```python
import torch

def _softmax(x, axis=-1):
    return torch.softmax(x, dim=axis)
def _gelu(x):
    return torch.nn.functional.gelu(x, approximate="tanh")
def _silu(x):
    return torch.nn.functional.silu(x)
def _sigmoid(x):
    return torch.sigmoid(x)
def _layernorm(x, axis=-1, eps=1e-5):
    m = x.mean(dim=axis, keepdim=True)
    v = x.var(dim=axis, keepdim=True, unbiased=False)
    return (x - m) / torch.sqrt(v + eps)
def _scatter_add(tgt, idx, src, axis=0):
    return tgt.clone().index_add_(axis, idx, src)
def _segment_sum(src, seg, n):
    out = torch.zeros((n,) + src.shape[1:], dtype=src.dtype)
    return out.index_add_(0, seg, src)
def _pad(x, pw):
    flat = tuple(v for pair in reversed(pw) for v in pair)
    return torch.nn.functional.pad(x, flat)

kernel_name = 'recurrent_scan__spectral_gfnet__swiglu_ffn__prompt'

def setup_inputs():

    _w = (lambda a: (lambda t: t.to(torch.bfloat16) if t.is_floating_point() else t)(torch.as_tensor(a)))
    def _A_setup():
        B, S, D = 1, 2048, 1024
        Df = D // 2 + 1
        return {
            "x": _w((lambda *s: torch.randn(*s, dtype=torch.bfloat16) * 0.05)(B, S, D)),
            "w_r": _w((lambda *s: torch.randn(*s, dtype=torch.bfloat16) * 0.05)(S, Df) * 0.02),
            "w_i": _w((lambda *s: torch.randn(*s, dtype=torch.bfloat16) * 0.05)(S, Df) * 0.02),
        }
    _A_in = _A_setup()

    def _B_setup():
        B, S, D, F = 1, 2048, 1024, 3584
        return {
            "x": _w((lambda *s: torch.randn(*s, dtype=torch.bfloat16) * 0.05)(B, S, D)),
            "w_gate": _w((lambda *s: torch.randn(*s, dtype=torch.bfloat16) * 0.05)(D, F)),
            "w_up": _w((lambda *s: torch.randn(*s, dtype=torch.bfloat16) * 0.05)(D, F)),
            "w_down": _w((lambda *s: torch.randn(*s, dtype=torch.bfloat16) * 0.05)(F, D)),
        }
    _B_in = _B_setup()

    return {
        "A_x": _A_in["x"],
        "A_w_r": _A_in["w_r"],
        "A_w_i": _A_in["w_i"],
        "B_x": _B_in["x"],
        "B_w_gate": _B_in["w_gate"],
        "B_w_up": _B_in["w_up"],
        "B_w_down": _B_in["w_down"],
    }

def reference(A_x, A_w_r, A_w_i, B_x, B_w_gate, B_w_up, B_w_down):
    def _A_ref(x, w_r, w_i):
        B, S, D = x.shape
        X = (lambda x, axes=(-2,-1): torch.fft.rfft2(x.float(), dim=axes))(x, axes=(-2, -1))
        W = w_r + 1j * w_i
        X = X * W
        y = (lambda x, s, axes=(-2,-1): torch.fft.irfft2(x, s=s, dim=axes).to(torch.bfloat16))(X, (S, D), axes=(-2, -1))
        return y

    def _B_ref(x, w_gate, w_up, w_down):
        g = _silu(x @ w_gate)
        u = x @ w_up
        return (g * u) @ w_down

    x = A_x
    xn = _layernorm(x, axis=-1)
    s = _A_ref(xn, A_w_r, A_w_i)
    g = _silu(_B_ref(xn, B_w_gate, B_w_up, B_w_down))
    return x + s * g
```

```cpp
#include <cuda.h>
#include <cuda_runtime.h>
#include <cuda_bf16.h>
#include <cuda_fp16.h>
#include <stdint.h>

__device__ __forceinline__ uint32_t smem_u32(const void* p) { return (uint32_t)__cvta_generic_to_shared(p); }
__device__ __forceinline__ void mbar_init(uint32_t bar, uint32_t cnt) { asm volatile("mbarrier.init.shared::cta.b64 [%0], %1;" :: "r"(bar), "r"(cnt)); }
__device__ __forceinline__ void mbar_expect_tx(uint32_t bar, uint32_t bytes) { asm volatile("mbarrier.arrive.expect_tx.shared::cta.b64 _, [%0], %1;" :: "r"(bar), "r"(bytes) : "memory"); }
__device__ __forceinline__ void mbar_arrive(uint32_t bar) { asm volatile("mbarrier.arrive.shared::cta.b64 _, [%0];" :: "r"(bar) : "memory"); }
__device__ __forceinline__ uint32_t mapa(uint32_t a, uint32_t cta) { uint32_t r; asm("mapa.shared::cluster.u32 %0, %1, %2;" : "=r"(r) : "r"(a), "r"(cta)); return r; }
__device__ __forceinline__ void mbar_wait(uint32_t bar, uint32_t parity) {
  asm volatile("{\n.reg .pred p;\n.reg .b32 n;\nmov.b32 n, 0;\n"
               "W_LOOP:\nadd.u32 n, n, 1;\nmbarrier.try_wait.parity.shared::cta.b64 p, [%0], %1;\nsetp.ge.or.u32 p, n, 1048576, p;\n@!p bra W_LOOP;\n}\n"
               :: "r"(bar), "r"(parity) : "memory");
}
__device__ __forceinline__ void tma_load_2d(uint32_t dst, const CUtensorMap* m, uint32_t bar, int c0, int c1) {
  asm volatile("cp.async.bulk.tensor.2d.shared::cluster.global.mbarrier::complete_tx::bytes [%0], [%1, {%3, %4}], [%2];"
    :: "r"(dst), "l"(m), "r"(bar), "r"(c0), "r"(c1) : "memory");
}
__device__ __forceinline__ void tma_store_2d(const CUtensorMap* m, uint32_t src, int c0, int c1) {
  asm volatile("cp.async.bulk.tensor.2d.global.shared::cta.bulk_group [%0, {%2, %3}], [%1];" :: "l"(m), "r"(src), "r"(c0), "r"(c1) : "memory");
}
__device__ __forceinline__ void prefetch_tmap(const CUtensorMap* m) { asm volatile("prefetch.tensormap [%0];" :: "l"(m) : "memory"); }
__device__ __forceinline__ void wgmma_fence() { asm volatile("wgmma.fence.sync.aligned;" ::: "memory"); }
__device__ __forceinline__ void wgmma_commit() { asm volatile("wgmma.commit_group.sync.aligned;" ::: "memory"); }
template<int N> __device__ __forceinline__ void wgmma_wait() { asm volatile("wgmma.wait_group.sync.aligned %0;" :: "n"(N) : "memory"); }
template<int R> __device__ __forceinline__ void reg_inc() { asm volatile("setmaxnreg.inc.sync.aligned.u32 %0;" :: "n"(R)); }
template<int R> __device__ __forceinline__ void reg_dec() { asm volatile("setmaxnreg.dec.sync.aligned.u32 %0;" :: "n"(R)); }
__device__ __forceinline__ uint32_t pack_bf16(float lo, float hi) { uint32_t r; asm("cvt.rn.bf16x2.f32 %0, %1, %2;" : "=r"(r) : "f"(hi), "f"(lo)); return r; }
__device__ __forceinline__ uint32_t hmul2_bf16(uint32_t a, uint32_t b) { uint32_t r; asm("mul.rn.bf16x2 %0, %1, %2;" : "=r"(r) : "r"(a), "r"(b)); return r; }
__device__ __forceinline__ float silu_half(float hh) { float t; asm("tanh.approx.f32 %0, %1;" : "=f"(t) : "f"(hh)); return fmaf(hh, t, hh); }
__device__ __forceinline__ float bf_lo(uint32_t u) { return __uint_as_float(u << 16); }
__device__ __forceinline__ float bf_hi(uint32_t u) { return __uint_as_float(u & 0xffff0000u); }
__device__ __forceinline__ float bf_round(float v) { return __bfloat162float(__float2bfloat16_rn(v)); }
__device__ __forceinline__ uint32_t ld_acquire(const uint32_t* p) { uint32_t v; asm volatile("ld.acquire.gpu.global.u32 %0, [%1];" : "=r"(v) : "l"(p) : "memory"); return v; }
__device__ __forceinline__ void red_release(uint32_t* p, uint32_t v) { asm volatile("red.release.gpu.global.add.u32 [%0], %1;" :: "l"(p), "r"(v) : "memory"); }
__device__ __forceinline__ void poll_cnt(const uint32_t* p, uint32_t target) {
  asm volatile("{\n.reg .pred p;\n.reg .b32 n, v;\nmov.b32 n, 0;\n"
               "P_LOOP:\nld.acquire.gpu.global.u32 v, [%0];\nadd.u32 n, n, 1;\nsetp.lt.u32 p, v, %1;\nsetp.lt.and.u32 p, n, 1048576, p;\n@p nanosleep.u32 40;\n@p bra P_LOOP;\n}\n"
               :: "l"(p), "r"(target) : "memory");
}
__device__ __forceinline__ void fence_proxy_async_global() { asm volatile("fence.proxy.async.global;" ::: "memory"); }
__device__ __forceinline__ void fence_proxy_async_smem() { asm volatile("fence.proxy.async.shared::cta;" ::: "memory"); }
__device__ __forceinline__ float sqrt_approx(float v) { float r; asm("sqrt.approx.f32 %0, %1;" : "=f"(r) : "f"(v)); return r; }
__device__ __forceinline__ int opaque(int v) { asm volatile("" : "+r"(v)); return v; }
__device__ __forceinline__ void bulk_load(uint32_t dst, const void* src, uint32_t bytes, uint32_t bar) {
  asm volatile("cp.async.bulk.shared::cluster.global.mbarrier::complete_tx::bytes [%0], [%1], %2, [%3];" :: "r"(dst), "l"(src), "r"(bytes), "r"(bar) : "memory");
}
__device__ __forceinline__ void tma_load_2d_mc(uint32_t dst, const CUtensorMap* m, uint32_t bar, int c0, int c1) {
  asm volatile("cp.async.bulk.tensor.2d.shared::cluster.global.mbarrier::complete_tx::bytes.multicast::cluster [%0], [%1, {%3, %4}], [%2], %5;"
    :: "r"(dst), "l"(m), "r"(bar), "r"(c0), "r"(c1), "h"((uint16_t)3) : "memory");
}
__device__ __forceinline__ void tma_load_5d_mc(uint32_t dst, const CUtensorMap* m, uint32_t bar, int c0, int c4) {
  asm volatile("cp.async.bulk.tensor.5d.shared::cluster.global.mbarrier::complete_tx::bytes.multicast::cluster [%0], [%1, {%3, %5, %5, %5, %4}], [%2], %6;"
    :: "r"(dst), "l"(m), "r"(bar), "r"(c0), "r"(c4), "r"(0), "h"((uint16_t)3) : "memory");
}
__device__ __forceinline__ void mbar_arrive_cl(uint32_t cl_addr) { asm volatile("mbarrier.arrive.shared::cluster.b64 _, [%0];" :: "r"(cl_addr) : "memory"); }
__device__ __forceinline__ void stg128(void* p, uint32_t a, uint32_t b, uint32_t c, uint32_t d) {
  asm volatile("st.global.v4.b32 [%0], {%1,%2,%3,%4};" :: "l"(p), "r"(a), "r"(b), "r"(c), "r"(d) : "memory");
}
__device__ __forceinline__ void tma_store_3d(const CUtensorMap* m, uint32_t src, int c0, int c1, int c2) {
  asm volatile("cp.async.bulk.tensor.3d.global.shared::cta.bulk_group [%0, {%2, %3, %4}], [%1];" :: "l"(m), "r"(src), "r"(c0), "r"(c1), "r"(c2) : "memory");
}
__device__ __forceinline__ void tma_load_3d(uint32_t dst, const CUtensorMap* m, uint32_t bar, int c0, int c1, int c2) {
  asm volatile("cp.async.bulk.tensor.3d.shared::cluster.global.mbarrier::complete_tx::bytes [%0], [%1, {%3, %4, %5}], [%2];"
    :: "r"(dst), "l"(m), "r"(bar), "r"(c0), "r"(c1), "r"(c2) : "memory");
}
__device__ __forceinline__ bool mbar_test(uint32_t bar, uint32_t parity) {
  uint32_t ok;
  asm volatile("{\n.reg .pred p;\nmbarrier.test_wait.parity.shared::cta.b64 p, [%1], %2;\nselp.u32 %0, 1, 0, p;\n}\n" : "=r"(ok) : "r"(bar), "r"(parity) : "memory");
  return ok;
}
__device__ __forceinline__ void mbar_wait_slow(uint32_t bar, uint32_t parity) { mbar_wait(bar, parity); }
__device__ __forceinline__ void smem_wait(uint32_t a, uint32_t target) {
  asm volatile("{\n.reg .pred p;\n.reg .b32 n, v;\nmov.b32 n, 0;\n"
               "S_LOOP:\nld.relaxed.cta.shared.u32 v, [%0];\nadd.u32 n, n, 1;\nsetp.lt.u32 p, v, %1;\nsetp.lt.and.u32 p, n, 4194304, p;\n@p nanosleep.u32 64;\n@p bra S_LOOP;\n}\n"
               :: "r"(a), "r"(target) : "memory");
}
template<int OA, int OB, int SD> __device__ __forceinline__ void wgmma_k64_n128(float (&d)[64], uint32_t da, uint32_t db) {
  asm volatile("{\n.reg .b32 ta, tb, hi;\n.reg .b64 a, b;\n.reg .pred p;\nsetp.ne.b32 p, %68, 0;\nmov.b32 hi, 0x40000040;\nadd.u32 ta, %64, %66;\nadd.u32 tb, %65, %67;\n"
    "mov.b64 a, {ta, hi};\nmov.b64 b, {tb, hi};\n"
    "wgmma.mma_async.sync.aligned.m64n128k16.f32.bf16.bf16 {%0, %1, %2, %3, %4, %5, %6, %7, %8, %9, %10, %11, %12, %13, %14, %15, %16, %17, %18, %19, %20, %21, %22, %23, %24, %25, %26, %27, %28, %29, %30, %31, %32, %33, %34, %35, %36, %37, %38, %39, %40, %41, %42, %43, %44, %45, %46, %47, %48, %49, %50, %51, %52, %53, %54, %55, %56, %57, %58, %59, %60, %61, %62, %63}, a, b, p, 1, 1, 0, 1;\nadd.u64 a, a, 2;\nadd.u64 b, b, 128;\n"
    "wgmma.mma_async.sync.aligned.m64n128k16.f32.bf16.bf16 {%0, %1, %2, %3, %4, %5, %6, %7, %8, %9, %10, %11, %12, %13, %14, %15, %16, %17, %18, %19, %20, %21, %22, %23, %24, %25, %26, %27, %28, %29, %30, %31, %32, %33, %34, %35, %36, %37, %38, %39, %40, %41, %42, %43, %44, %45, %46, %47, %48, %49, %50, %51, %52, %53, %54, %55, %56, %57, %58, %59, %60, %61, %62, %63}, a, b, 1, 1, 1, 0, 1;\nadd.u64 a, a, 2;\nadd.u64 b, b, 128;\n"
    "wgmma.mma_async.sync.aligned.m64n128k16.f32.bf16.bf16 {%0, %1, %2, %3, %4, %5, %6, %7, %8, %9, %10, %11, %12, %13, %14, %15, %16, %17, %18, %19, %20, %21, %22, %23, %24, %25, %26, %27, %28, %29, %30, %31, %32, %33, %34, %35, %36, %37, %38, %39, %40, %41, %42, %43, %44, %45, %46, %47, %48, %49, %50, %51, %52, %53, %54, %55, %56, %57, %58, %59, %60, %61, %62, %63}, a, b, 1, 1, 1, 0, 1;\nadd.u64 a, a, 2;\nadd.u64 b, b, 128;\n"
    "wgmma.mma_async.sync.aligned.m64n128k16.f32.bf16.bf16 {%0, %1, %2, %3, %4, %5, %6, %7, %8, %9, %10, %11, %12, %13, %14, %15, %16, %17, %18, %19, %20, %21, %22, %23, %24, %25, %26, %27, %28, %29, %30, %31, %32, %33, %34, %35, %36, %37, %38, %39, %40, %41, %42, %43, %44, %45, %46, %47, %48, %49, %50, %51, %52, %53, %54, %55, %56, %57, %58, %59, %60, %61, %62, %63}, a, b, 1, 1, 1, 0, 1;\n}\n"
    : "+f"(d[0]), "+f"(d[1]), "+f"(d[2]), "+f"(d[3]), "+f"(d[4]), "+f"(d[5]), "+f"(d[6]), "+f"(d[7]), "+f"(d[8]), "+f"(d[9]), "+f"(d[10]), "+f"(d[11]), "+f"(d[12]), "+f"(d[13]), "+f"(d[14]), "+f"(d[15]), "+f"(d[16]), "+f"(d[17]), "+f"(d[18]), "+f"(d[19]), "+f"(d[20]), "+f"(d[21]), "+f"(d[22]), "+f"(d[23]), "+f"(d[24]), "+f"(d[25]), "+f"(d[26]), "+f"(d[27]), "+f"(d[28]), "+f"(d[29]), "+f"(d[30]), "+f"(d[31]), "+f"(d[32]), "+f"(d[33]), "+f"(d[34]), "+f"(d[35]), "+f"(d[36]), "+f"(d[37]), "+f"(d[38]), "+f"(d[39]), "+f"(d[40]), "+f"(d[41]), "+f"(d[42]), "+f"(d[43]), "+f"(d[44]), "+f"(d[45]), "+f"(d[46]), "+f"(d[47]), "+f"(d[48]), "+f"(d[49]), "+f"(d[50]), "+f"(d[51]), "+f"(d[52]), "+f"(d[53]), "+f"(d[54]), "+f"(d[55]), "+f"(d[56]), "+f"(d[57]), "+f"(d[58]), "+f"(d[59]), "+f"(d[60]), "+f"(d[61]), "+f"(d[62]), "+f"(d[63])
    : "r"(da), "r"(db), "n"(OA), "n"(OB), "n"(SD));
}

template<int OA, int OB, int SD> __device__ __forceinline__ void wgmma_k64_n256(float (&d)[128], uint32_t da, uint32_t db) {
  asm volatile("{\n.reg .b32 ta, tb, hi;\n.reg .b64 a, b;\n.reg .pred p;\nsetp.ne.b32 p, %132, 0;\nmov.b32 hi, 0x40000040;\nadd.u32 ta, %128, %130;\nadd.u32 tb, %129, %131;\n"
    "mov.b64 a, {ta, hi};\nmov.b64 b, {tb, hi};\n"
    "wgmma.mma_async.sync.aligned.m64n256k16.f32.bf16.bf16 {%0, %1, %2, %3, %4, %5, %6, %7, %8, %9, %10, %11, %12, %13, %14, %15, %16, %17, %18, %19, %20, %21, %22, %23, %24, %25, %26, %27, %28, %29, %30, %31, %32, %33, %34, %35, %36, %37, %38, %39, %40, %41, %42, %43, %44, %45, %46, %47, %48, %49, %50, %51, %52, %53, %54, %55, %56, %57, %58, %59, %60, %61, %62, %63, %64, %65, %66, %67, %68, %69, %70, %71, %72, %73, %74, %75, %76, %77, %78, %79, %80, %81, %82, %83, %84, %85, %86, %87, %88, %89, %90, %91, %92, %93, %94, %95, %96, %97, %98, %99, %100, %101, %102, %103, %104, %105, %106, %107, %108, %109, %110, %111, %112, %113, %114, %115, %116, %117, %118, %119, %120, %121, %122, %123, %124, %125, %126, %127}, a, b, p, 1, 1, 0, 1;\nadd.u64 a, a, 2;\nadd.u64 b, b, 128;\n"
    "wgmma.mma_async.sync.aligned.m64n256k16.f32.bf16.bf16 {%0, %1, %2, %3, %4, %5, %6, %7, %8, %9, %10, %11, %12, %13, %14, %15, %16, %17, %18, %19, %20, %21, %22, %23, %24, %25, %26, %27, %28, %29, %30, %31, %32, %33, %34, %35, %36, %37, %38, %39, %40, %41, %42, %43, %44, %45, %46, %47, %48, %49, %50, %51, %52, %53, %54, %55, %56, %57, %58, %59, %60, %61, %62, %63, %64, %65, %66, %67, %68, %69, %70, %71, %72, %73, %74, %75, %76, %77, %78, %79, %80, %81, %82, %83, %84, %85, %86, %87, %88, %89, %90, %91, %92, %93, %94, %95, %96, %97, %98, %99, %100, %101, %102, %103, %104, %105, %106, %107, %108, %109, %110, %111, %112, %113, %114, %115, %116, %117, %118, %119, %120, %121, %122, %123, %124, %125, %126, %127}, a, b, 1, 1, 1, 0, 1;\nadd.u64 a, a, 2;\nadd.u64 b, b, 128;\n"
    "wgmma.mma_async.sync.aligned.m64n256k16.f32.bf16.bf16 {%0, %1, %2, %3, %4, %5, %6, %7, %8, %9, %10, %11, %12, %13, %14, %15, %16, %17, %18, %19, %20, %21, %22, %23, %24, %25, %26, %27, %28, %29, %30, %31, %32, %33, %34, %35, %36, %37, %38, %39, %40, %41, %42, %43, %44, %45, %46, %47, %48, %49, %50, %51, %52, %53, %54, %55, %56, %57, %58, %59, %60, %61, %62, %63, %64, %65, %66, %67, %68, %69, %70, %71, %72, %73, %74, %75, %76, %77, %78, %79, %80, %81, %82, %83, %84, %85, %86, %87, %88, %89, %90, %91, %92, %93, %94, %95, %96, %97, %98, %99, %100, %101, %102, %103, %104, %105, %106, %107, %108, %109, %110, %111, %112, %113, %114, %115, %116, %117, %118, %119, %120, %121, %122, %123, %124, %125, %126, %127}, a, b, 1, 1, 1, 0, 1;\nadd.u64 a, a, 2;\nadd.u64 b, b, 128;\n"
    "wgmma.mma_async.sync.aligned.m64n256k16.f32.bf16.bf16 {%0, %1, %2, %3, %4, %5, %6, %7, %8, %9, %10, %11, %12, %13, %14, %15, %16, %17, %18, %19, %20, %21, %22, %23, %24, %25, %26, %27, %28, %29, %30, %31, %32, %33, %34, %35, %36, %37, %38, %39, %40, %41, %42, %43, %44, %45, %46, %47, %48, %49, %50, %51, %52, %53, %54, %55, %56, %57, %58, %59, %60, %61, %62, %63, %64, %65, %66, %67, %68, %69, %70, %71, %72, %73, %74, %75, %76, %77, %78, %79, %80, %81, %82, %83, %84, %85, %86, %87, %88, %89, %90, %91, %92, %93, %94, %95, %96, %97, %98, %99, %100, %101, %102, %103, %104, %105, %106, %107, %108, %109, %110, %111, %112, %113, %114, %115, %116, %117, %118, %119, %120, %121, %122, %123, %124, %125, %126, %127}, a, b, 1, 1, 1, 0, 1;\n}\n"
    : "+f"(d[0]), "+f"(d[1]), "+f"(d[2]), "+f"(d[3]), "+f"(d[4]), "+f"(d[5]), "+f"(d[6]), "+f"(d[7]), "+f"(d[8]), "+f"(d[9]), "+f"(d[10]), "+f"(d[11]), "+f"(d[12]), "+f"(d[13]), "+f"(d[14]), "+f"(d[15]), "+f"(d[16]), "+f"(d[17]), "+f"(d[18]), "+f"(d[19]), "+f"(d[20]), "+f"(d[21]), "+f"(d[22]), "+f"(d[23]), "+f"(d[24]), "+f"(d[25]), "+f"(d[26]), "+f"(d[27]), "+f"(d[28]), "+f"(d[29]), "+f"(d[30]), "+f"(d[31]), "+f"(d[32]), "+f"(d[33]), "+f"(d[34]), "+f"(d[35]), "+f"(d[36]), "+f"(d[37]), "+f"(d[38]), "+f"(d[39]), "+f"(d[40]), "+f"(d[41]), "+f"(d[42]), "+f"(d[43]), "+f"(d[44]), "+f"(d[45]), "+f"(d[46]), "+f"(d[47]), "+f"(d[48]), "+f"(d[49]), "+f"(d[50]), "+f"(d[51]), "+f"(d[52]), "+f"(d[53]), "+f"(d[54]), "+f"(d[55]), "+f"(d[56]), "+f"(d[57]), "+f"(d[58]), "+f"(d[59]), "+f"(d[60]), "+f"(d[61]), "+f"(d[62]), "+f"(d[63]), "+f"(d[64]), "+f"(d[65]), "+f"(d[66]), "+f"(d[67]), "+f"(d[68]), "+f"(d[69]), "+f"(d[70]), "+f"(d[71]), "+f"(d[72]), "+f"(d[73]), "+f"(d[74]), "+f"(d[75]), "+f"(d[76]), "+f"(d[77]), "+f"(d[78]), "+f"(d[79]), "+f"(d[80]), "+f"(d[81]), "+f"(d[82]), "+f"(d[83]), "+f"(d[84]), "+f"(d[85]), "+f"(d[86]), "+f"(d[87]), "+f"(d[88]), "+f"(d[89]), "+f"(d[90]), "+f"(d[91]), "+f"(d[92]), "+f"(d[93]), "+f"(d[94]), "+f"(d[95]), "+f"(d[96]), "+f"(d[97]), "+f"(d[98]), "+f"(d[99]), "+f"(d[100]), "+f"(d[101]), "+f"(d[102]), "+f"(d[103]), "+f"(d[104]), "+f"(d[105]), "+f"(d[106]), "+f"(d[107]), "+f"(d[108]), "+f"(d[109]), "+f"(d[110]), "+f"(d[111]), "+f"(d[112]), "+f"(d[113]), "+f"(d[114]), "+f"(d[115]), "+f"(d[116]), "+f"(d[117]), "+f"(d[118]), "+f"(d[119]), "+f"(d[120]), "+f"(d[121]), "+f"(d[122]), "+f"(d[123]), "+f"(d[124]), "+f"(d[125]), "+f"(d[126]), "+f"(d[127])
    : "r"(da), "r"(db), "n"(OA), "n"(OB), "n"(SD));
}

typedef __half2 h2;
__device__ __forceinline__ h2 u2h(uint32_t u) { return *reinterpret_cast<h2*>(&u); }
__device__ __forceinline__ uint32_t h2u(h2 h) { return *reinterpret_cast<uint32_t*>(&h); }
__device__ __forceinline__ h2 pack_h2(float lo, float hi) { uint32_t r; asm("cvt.rn.f16x2.f32 %0, %1, %2;" : "=r"(r) : "f"(hi), "f"(lo)); return u2h(r); }
#define H2_R   u2h(0x39A839A8u)
#define H2_C1  u2h(0x3B643B64u)
#define H2_S1  u2h(0x361F361Fu)

__device__ __forceinline__ void bfly4(h2& ar, h2& ai, h2& br, h2& bi, h2& cr, h2& ci, h2& dr, h2& di) {
  h2 t0r = __hadd2(ar, cr), t0i = __hadd2(ai, ci), t1r = __hsub2(ar, cr), t1i = __hsub2(ai, ci);
  h2 t2r = __hadd2(br, dr), t2i = __hadd2(bi, di), t3r = __hsub2(br, dr), t3i = __hsub2(bi, di);
  ar = __hadd2(t0r, t2r); ai = __hadd2(t0i, t2i);
  cr = __hsub2(t0r, t2r); ci = __hsub2(t0i, t2i);
  br = __hadd2(t1r, t3i); bi = __hsub2(t1i, t3r);
  dr = __hsub2(t1r, t3i); di = __hadd2(t1i, t3r);
}
__device__ __forceinline__ void cmul_cs(h2& zr, h2& zi, h2 c, h2 s) {
  const h2 t = __hmul2(zi, s), u = __hmul2(zr, s);
  zr = __hfma2(zr, c, t);
  zi = __hfma2(zi, c, __hneg2(u));
}
__device__ __forceinline__ void cmul(h2& zr, h2& zi, h2 wr, h2 wi) {
  const h2 t = __hmul2(zi, wi), u = __hmul2(zr, wi);
  zr = __hfma2(zr, wr, __hneg2(t));
  zi = __hfma2(zi, wr, u);
}
__device__ __forceinline__ void fft16(h2 (&r)[16], h2 (&i)[16]) {
#pragma unroll
  for (int n = 0; n < 4; n++) bfly4(r[n], i[n], r[n+4], i[n+4], r[n+8], i[n+8], r[n+12], i[n+12]);
  cmul_cs(r[5], i[5], H2_C1, H2_S1);
  { h2 a = __hadd2(r[6], i[6]), b = __hsub2(i[6], r[6]); r[6] = __hmul2(a, H2_R); i[6] = __hmul2(b, H2_R); }
  cmul_cs(r[7], i[7], H2_S1, H2_C1);
  { h2 a = __hadd2(r[9], i[9]), b = __hsub2(i[9], r[9]); r[9] = __hmul2(a, H2_R); i[9] = __hmul2(b, H2_R); }
  { h2 a = r[10]; r[10] = i[10]; i[10] = __hneg2(a); }
  { h2 a = __hsub2(i[11], r[11]), b = __hadd2(i[11], r[11]); r[11] = __hmul2(a, H2_R); i[11] = __hmul2(b, __hneg2(H2_R)); }
  cmul_cs(r[13], i[13], H2_S1, H2_C1);
  { h2 a = __hsub2(i[14], r[14]), b = __hadd2(i[14], r[14]); r[14] = __hmul2(a, H2_R); i[14] = __hmul2(b, __hneg2(H2_R)); }
  cmul_cs(r[15], i[15], __hneg2(H2_C1), __hneg2(H2_S1));
#pragma unroll
  for (int k = 0; k < 4; k++) bfly4(r[4*k], i[4*k], r[4*k+1], i[4*k+1], r[4*k+2], i[4*k+2], r[4*k+3], i[4*k+3]);
#pragma unroll
  for (int a = 0; a < 4; a++)
#pragma unroll
    for (int b = a + 1; b < 4; b++) {
      h2 t = r[4*a+b]; r[4*a+b] = r[4*b+a]; r[4*b+a] = t;
      t = i[4*a+b]; i[4*a+b] = i[4*b+a]; i[4*b+a] = t;
    }
}

__device__ __forceinline__ void sts64(uint32_t a, h2 x, h2 y) { asm volatile("st.shared.v2.b32 [%0], {%1,%2};" :: "r"(a), "r"(h2u(x)), "r"(h2u(y)) : "memory"); }
__device__ __forceinline__ void sts128(uint32_t a, uint32_t x, uint32_t y, uint32_t z, uint32_t w) { asm volatile("st.shared.v4.b32 [%0], {%1,%2,%3,%4};" :: "r"(a), "r"(x), "r"(y), "r"(z), "r"(w) : "memory"); }
__device__ __forceinline__ void lds64(uint32_t a, h2& x, h2& y) { uint32_t u, v; asm volatile("ld.shared.v2.b32 {%0,%1}, [%2];" : "=r"(u), "=r"(v) : "r"(a) : "memory"); x = u2h(u); y = u2h(v); }
__device__ __forceinline__ void lds128(uint32_t a, h2& x, h2& y, h2& z, h2& w) { uint32_t p, q, r, s; asm volatile("ld.shared.v4.b32 {%0,%1,%2,%3}, [%4];" : "=r"(p), "=r"(q), "=r"(r), "=r"(s) : "r"(a) : "memory"); x = u2h(p); y = u2h(q); z = u2h(r); w = u2h(s); }
__device__ __forceinline__ uint2 ldg64(const uint2* p) { uint2 v; asm volatile("ld.global.cg.v2.b32 {%0,%1}, [%2];" : "=r"(v.x), "=r"(v.y) : "l"(p) : "memory"); return v; }
__device__ __forceinline__ uint4 ldg128(const uint4* p) { uint4 v; asm volatile("ld.global.cg.v4.b32 {%0,%1,%2,%3}, [%4];" : "=r"(v.x), "=r"(v.y), "=r"(v.z), "=r"(v.w) : "l"(p) : "memory"); return v; }
__device__ __forceinline__ void side_bar() { asm volatile("bar.sync 2, 96;" ::: "memory"); }

constexpr int NSIDE = 3;
constexpr int ZWORDS = 4 * 256 * 128 * 4;
constexpr int WROW = 516;

__device__ __forceinline__ constexpr uint32_t swz(int i) { return (uint32_t)(((i & 7) << 5) | (((i >> 2) & 1) << 4)); }

constexpr float TWO_PI = 6.283185307179586f;
__device__ __forceinline__ void build_tw256(int tid, int nt, uint32_t tab, float scale) {
#pragma unroll 1
  for (int e = 16 + tid; e < 256; e += nt) {
    const int m = (e >> 4) * (e & 15);
    float s, c; __sincosf((float)(m > 128 ? m - 256 : m) * (TWO_PI / 256.f), &s, &c);
    sts64(tab + e * 8, pack_h2(c * scale, c * scale), pack_h2(s * scale, s * scale));
  }
}
__device__ __forceinline__ void build_tb(int tid, uint32_t tab) {
#pragma unroll 1
  for (int e = tid; e < 256; e += 32) {
    const int be = e & 7, i = e >> 4;
    int m0, m1; float sc;
    if (e & 8) { m0 = 16 * i + be; m1 = m0 + 8; sc = 1.f; }
    else { m0 = 2 * be * i; m1 = m0 + 16 * i; sc = 0.125f; }
    float s0, c0, s1, c1;
    __sincosf((float)(m0 > 256 ? m0 - 512 : m0) * (TWO_PI / 512.f), &s0, &c0);
    __sincosf((float)(m1 > 256 ? m1 - 512 : m1) * (TWO_PI / 512.f), &s1, &c1);
    sts64(tab + e * 8, pack_h2(c0 * sc, c1 * sc), pack_h2(s0 * sc, s1 * sc));
  }
}
__device__ __forceinline__ void make_omega(int cta, h2 (&oc)[3], h2 (&os)[3]) {
  const int s0 = (cta >> 3) * 16 + (cta & 7);
#pragma unroll
  for (int t = 1; t <= 3; t++) {
    float s0f, c0f, s1f, c1f;
    __sincosf((float)(s0 * t) * (TWO_PI / 2048.f), &s0f, &c0f);
    __sincosf((float)((s0 + 8) * t) * (TWO_PI / 2048.f), &s1f, &c1f);
    oc[t-1] = pack_h2(c0f, c1f); os[t-1] = pack_h2(s0f, s1f);
  }
}

__device__ __forceinline__ uint32_t hsub2_bf16(uint32_t a, uint32_t b) { uint32_t r; asm("sub.rn.bf16x2 %0, %1, %2;" : "=r"(r) : "r"(a), "r"(b)); return r; }
__device__ __forceinline__ uint4 ldg_nc128(const uint4* p) { uint4 v; asm volatile("ld.global.nc.v4.b32 {%0,%1,%2,%3}, [%4];" : "=r"(v.x), "=r"(v.y), "=r"(v.z), "=r"(v.w) : "l"(p)); return v; }

__device__ __forceinline__ void ln_load(int j, int lane, uint32_t buf, uint32_t (&raw)[32]) {
#pragma unroll
  for (int i = 0; i < 8; i++)
    asm volatile("ld.shared.v4.b32 {%0,%1,%2,%3}, [%4];" : "=r"(raw[i*4]), "=r"(raw[i*4+1]), "=r"(raw[i*4+2]), "=r"(raw[i*4+3]) : "r"(buf + j * 4096 + i * 512 + lane * 16) : "memory");
}
__device__ __forceinline__ void ln_sums(const uint32_t (&raw)[32], float (&piv)[2], float (&sm)[2], float (&sq)[2]) {
  float s[2][4], q[2][4];
#pragma unroll
  for (int r = 0; r < 2; r++) {
    piv[r] = bf_lo(__shfl_sync(0xffffffff, raw[r*16], 0));
#pragma unroll
    for (int k = 0; k < 4; k++) { s[r][k] = 0.f; q[r][k] = 0.f; }
  }
#pragma unroll
  for (int e = 0; e < 16; e++)
#pragma unroll
    for (int r = 0; r < 2; r++) {
      const float a = bf_lo(raw[r*16+e]) - piv[r], b = bf_hi(raw[r*16+e]) - piv[r];
      const int k = (e & 1) * 2;
      s[r][k] += a; s[r][k+1] += b; q[r][k] = fmaf(a, a, q[r][k]); q[r][k+1] = fmaf(b, b, q[r][k+1]);
    }
  float v0 = (s[0][0] + s[0][1]) + (s[0][2] + s[0][3]), v1 = (s[1][0] + s[1][1]) + (s[1][2] + s[1][3]);
  float v2 = (q[0][0] + q[0][1]) + (q[0][2] + q[0][3]), v3 = (q[1][0] + q[1][1]) + (q[1][2] + q[1][3]);
#pragma unroll
  for (int o = 16; o; o >>= 1) {
    v0 += __shfl_xor_sync(0xffffffff, v0, o); v1 += __shfl_xor_sync(0xffffffff, v1, o);
    v2 += __shfl_xor_sync(0xffffffff, v2, o); v3 += __shfl_xor_sync(0xffffffff, v3, o);
  }
  sm[0] = v0; sm[1] = v1; sq[0] = v2; sq[1] = v3;
}
__device__ __forceinline__ void ln_stats(int cta, int j, int lane, const float (&piv)[2], const float (&sm)[2], const float (&sq)[2],
                                         float2* __restrict__ stats, float (&inv)[2], uint32_t (&mb2)[2]) {
#pragma unroll
  for (int r = 0; r < 2; r++) {
    const float dm = sm[r] * (1.f / 1024.f);
    const float var = fmaxf(fmaf(-dm, dm, sq[r] * (1.f / 1024.f)), 0.f);
    mb2[r] = pack_bf16(piv[r] + dm, piv[r] + dm);
    inv[r] = __fdividef(0.5f, bf_round(sqrt_approx(bf_round(bf_round(var) + 1e-5f))));
  }
  const int row = (cta >> 3) * 16 + (cta & 7) + 256 * j;
  if (lane < 2) stats[row + 8 * lane] = lane ? make_float2(inv[1], -bf_lo(mb2[1])) : make_float2(inv[0], -bf_lo(mb2[0]));
}
template<int H>
__device__ __forceinline__ void ln_apply(int cta, int j, int lane, uint32_t buf, uint32_t (&raw)[32], __nv_bfloat16* __restrict__ xn,
                                         const float (&inv)[2], const uint32_t (&mb2)[2]) {
  const int a = lane >> 1;
  const uint32_t sa = buf + (j >> 1) * 8192 + (a >> 3) * 4096 + (lane & 1) * 2048 + (swz(a) ^ ((j & 1) << 4));
#pragma unroll
  for (int e2 = 2 * H; e2 < 2 * H + 2; e2++) {
    uint32_t lo[4], hi[4];
#pragma unroll
    for (int c = 0; c < 4; c++) {
      const uint32_t d0 = hsub2_bf16(raw[c*4+e2], mb2[0]), d1 = hsub2_bf16(raw[16+c*4+e2], mb2[1]);
      const float a0 = bf_lo(d0) * inv[0], b0 = bf_hi(d0) * inv[0], a1 = bf_lo(d1) * inv[1], b1 = bf_hi(d1) * inv[1];
      raw[c*4+e2] = pack_bf16(a0, b0); raw[16+c*4+e2] = pack_bf16(a1, b1);
      lo[c] = h2u(pack_h2(a0, a1)); hi[c] = h2u(pack_h2(b0, b1));
    }
    sts128((sa ^ swz(2*e2)) + 2*e2 * 256, lo[0], lo[1], lo[2], lo[3]);
    sts128((sa ^ swz(2*e2+1)) + (2*e2+1) * 256, hi[0], hi[1], hi[2], hi[3]);
  }
  if (H == 1) {
    uint4* po = reinterpret_cast<uint4*>(xn) + ((cta >> 3) * 16 + (cta & 7) + 256 * j) * 128 + lane;
#pragma unroll
    for (int i = 0; i < 8; i++) stg128(po + (i >> 2) * 1024 + (i & 3) * 32, raw[i*4], raw[i*4+1], raw[i*4+2], raw[i*4+3]);
  }
}
__device__ __forceinline__ void colsum64(int cta, int w, int lane, const __nv_bfloat16* __restrict__ wg, const __nv_bfloat16* __restrict__ wu, float* __restrict__ cs) {
  const int part = cta >> 5, cg = cta & 31;
  const uint4* p = reinterpret_cast<const uint4*>(((cg & 1) ? wu : wg) + (cg >> 1) * 64) + (lane & 7) + (part * 256 + (lane >> 3)) * 448;
  float a[8];
#pragma unroll
  for (int e = 0; e < 8; e++) a[e] = 0.f;
#pragma unroll 1
  for (int i0 = w; i0 < 64; i0 += 11 * NSIDE) {
    uint4 v[11];
#pragma unroll
    for (int u = 0; u < 11; u++) v[u] = ldg_nc128(p + min(i0 + u * NSIDE, 63) * 4 * 448);
    if (i0 + 10 * NSIDE > 63) v[10] = make_uint4(0, 0, 0, 0);
#pragma unroll
    for (int u = 0; u < 11; u++) {
      a[0] += bf_lo(v[u].x); a[1] += bf_hi(v[u].x); a[2] += bf_lo(v[u].y); a[3] += bf_hi(v[u].y);
      a[4] += bf_lo(v[u].z); a[5] += bf_hi(v[u].z); a[6] += bf_lo(v[u].w); a[7] += bf_hi(v[u].w);
    }
  }
#pragma unroll
  for (int o = 16; o >= 8; o >>= 1)
#pragma unroll
    for (int e = 0; e < 8; e++) a[e] += __shfl_xor_sync(0xffffffff, a[e], o);
  if (lane < 8) {
    float* d = cs + cg * 64 + lane * 8;
    asm volatile("red.global.add.v4.f32 [%0], {%1,%2,%3,%4};" :: "l"(d), "f"(a[0]), "f"(a[1]), "f"(a[2]), "f"(a[3]) : "memory");
    asm volatile("red.global.add.v4.f32 [%0], {%1,%2,%3,%4};" :: "l"(d + 4), "f"(a[4]), "f"(a[5]), "f"(a[6]), "f"(a[7]) : "memory");
  }
}

__device__ __forceinline__ void pass_a0(int cta, int w, int lane, uint32_t buf) {
  h2 oc[3], os[3];
  make_omega(cta, oc, os);
#pragma unroll 1
  for (int it = w; it < 8; it += NSIDE) {
    const int n0 = it * 32 + lane;
    h2 yr[4][4], yi[4][4];
    const uint32_t p0 = buf + (it >> 2) * 4096 + (lane & 15) * 256 + (swz(n0 >> 4) ^ swz(lane)), p1 = p0 ^ 16;
    h2 xin[8][4];
#pragma unroll
    for (int j = 0; j < 8; j++) lds128(((j & 1) ? p1 : p0) + (j >> 1) * 8192, xin[j][0], xin[j][1], xin[j][2], xin[j][3]);
    float s1, c1f; __sincosf((float)n0 * (TWO_PI / 1024.f), &s1, &c1f);
    const float c2f = c1f * c1f - s1 * s1, s2 = 2.f * c1f * s1, c3f = c2f * c1f - s2 * s1, s3 = s2 * c1f + c2f * s1;
    const h2 wc1 = pack_h2(c1f, c1f), ws1 = pack_h2(s1, s1), wc2 = pack_h2(c2f, c2f), ws2 = pack_h2(s2, s2), wc3 = pack_h2(c3f, c3f), ws3 = pack_h2(s3, s3);
#pragma unroll
    for (int jn = 0; jn < 4; jn++) {
      h2 x[8];
#pragma unroll
      for (int j = 0; j < 8; j++) x[j] = xin[j][jn];
      h2 a0 = __hadd2(x[0], x[4]), a1 = __hadd2(x[1], x[5]), a2 = __hadd2(x[2], x[6]), a3 = __hadd2(x[3], x[7]);
      h2 b0 = __hsub2(x[0], x[4]), b1 = __hsub2(x[1], x[5]), b2 = __hsub2(x[2], x[6]), b3 = __hsub2(x[3], x[7]);
      h2 c0 = __hadd2(a0, a2), c1 = __hadd2(a1, a3);
      yr[0][jn] = __hadd2(c0, c1); yi[0][jn] = __hsub2(c0, c1);
      yr[2][jn] = __hsub2(a0, a2); yi[2][jn] = __hsub2(a3, a1);
      h2 t1 = __hsub2(b1, b3), t2 = __hadd2(b1, b3);
      yr[1][jn] = __hfma2(t1, H2_R, b0); yi[1][jn] = __hfma2(t2, __hneg2(H2_R), __hneg2(b2));
      yr[3][jn] = __hfma2(t1, __hneg2(H2_R), b0); yi[3][jn] = __hfma2(t2, __hneg2(H2_R), b2);
#pragma unroll
      for (int t = 1; t <= 3; t++) cmul_cs(yr[t][jn], yi[t][jn], oc[t-1], os[t-1]);
    }
#pragma unroll
    for (int ch = 0; ch < 4; ch++) {
      bfly4(yr[ch][0], yi[ch][0], yr[ch][1], yi[ch][1], yr[ch][2], yi[ch][2], yr[ch][3], yi[ch][3]);
      cmul_cs(yr[ch][1], yi[ch][1], wc1, ws1);
      cmul_cs(yr[ch][2], yi[ch][2], wc2, ws2);
      cmul_cs(yr[ch][3], yi[ch][3], wc3, ws3);
      sts128(p0 + ch * 8192, h2u(yr[ch][0]), h2u(yi[ch][0]), h2u(yr[ch][1]), h2u(yi[ch][1]));
      sts128(p1 + ch * 8192, h2u(yr[ch][2]), h2u(yi[ch][2]), h2u(yr[ch][3]), h2u(yi[ch][3]));
    }
  }
}

__device__ __forceinline__ void pass_c0(int cta, int w, int lane, uint32_t buf, uint32_t* __restrict__ sfrag) {
  h2 oc[3], os[3];
  make_omega(cta, oc, os);
#pragma unroll 1
  for (int it = w; it < 8; it += NSIDE) {
    const int n0 = it * 32 + lane;
    float s1, c1f; __sincosf((float)n0 * (TWO_PI / 1024.f), &s1, &c1f);
    const float c2f = c1f * c1f - s1 * s1, s2 = 2.f * c1f * s1, c3f = c2f * c1f - s2 * s1, s3 = s2 * c1f + c2f * s1;
    const h2 wc1 = pack_h2(c1f, c1f), ws1 = pack_h2(s1, s1), wc2 = pack_h2(c2f, c2f), ws2 = pack_h2(s2, s2), wc3 = pack_h2(c3f, c3f), ws3 = pack_h2(s3, s3);
    h2 yr[4][4], yi[4][4];
    const uint32_t p0 = buf + (it >> 2) * 4096 + (lane & 15) * 256 + (swz(n0 >> 4) ^ swz(lane)), p1 = p0 ^ 16;
#pragma unroll
    for (int ch = 0; ch < 4; ch++) {
      lds128(p0 + ch * 8192, yi[ch][0], yr[ch][0], yi[ch][1], yr[ch][1]);
      lds128(p1 + ch * 8192, yi[ch][2], yr[ch][2], yi[ch][3], yr[ch][3]);
      cmul(yr[ch][1], yi[ch][1], wc1, ws1);
      cmul(yr[ch][2], yi[ch][2], wc2, ws2);
      cmul(yr[ch][3], yi[ch][3], wc3, ws3);
      bfly4(yi[ch][0], yr[ch][0], yi[ch][1], yr[ch][1], yi[ch][2], yr[ch][2], yi[ch][3], yr[ch][3]);
    }
    const int pn = (n0 & ~15) | ((n0 & 6) << 1) | ((n0 & 8) >> 2) | (n0 & 1);
    uint32_t* dst = sfrag + (size_t)cta * 1024 + pn;
#pragma unroll
    for (int jn = 0; jn < 4; jn++) {
#pragma unroll
      for (int t = 1; t <= 3; t++) cmul(yr[t][jn], yi[t][jn], oc[t-1], os[t-1]);
      h2 p = __hadd2(yr[0][jn], yi[0][jn]), m = __hsub2(yr[0][jn], yi[0][jn]);
      h2 e0 = __hadd2(p, yr[2][jn]), e2 = __hsub2(p, yr[2][jn]), e1 = __hsub2(m, yi[2][jn]), e3 = __hadd2(m, yi[2][jn]);
      h2 o0 = __hadd2(yr[1][jn], yr[3][jn]), o2 = __hsub2(yi[3][jn], yi[1][jn]);
      h2 u = __hsub2(yr[1][jn], yr[3][jn]), v = __hadd2(yi[1][jn], yi[3][jn]);
      h2 o1 = __hsub2(u, v), o3 = __hadd2(u, v);
      h2 x[8];
      x[0] = __hadd2(e0, o0); x[4] = __hsub2(e0, o0);
      x[1] = __hfma2(o1, H2_R, e1); x[5] = __hfma2(o1, __hneg2(H2_R), e1);
      x[2] = __hadd2(e2, o2); x[6] = __hsub2(e2, o2);
      x[3] = __hfma2(o3, __hneg2(H2_R), e3); x[7] = __hfma2(o3, H2_R, e3);
#pragma unroll
      for (int j = 0; j < 8; j++) dst[j * 128 * 1024 + 256 * jn] = h2u(x[j]);
    }
  }
}

__device__ __forceinline__ int b_unit(int cta, int w, int k) {
  if (w == 0) return cta;
  return (k == 2 ? 3 : 1 + ((k + w + 1) & 1)) * 256 + cta * 2 + w - 1;
}
__device__ __forceinline__ uint32_t wexp_from_max(uint32_t maxbits) { return min(max(maxbits >> 7, 16u), 230u); }
__device__ __forceinline__ uint32_t ldg32(const void* p) { uint32_t v; asm volatile("ld.global.cg.b32 %0, [%1];" : "=r"(v) : "l"(p) : "memory"); return v; }
__device__ __forceinline__ uint32_t mirror_off(int cta, int lane) {
  const int qm = (1024 - (cta * 4 + (lane & 3))) & 1023;
  return (qm >> 2) * 512 + (lane & 28) + (qm & 3);
}
template<int ID, int N> __device__ __forceinline__ void nb_arrive() { asm volatile("bar.arrive %0, %1;" :: "n"(ID), "n"(N) : "memory"); }
template<int ID, int N> __device__ __forceinline__ void nb_sync() { asm volatile("bar.sync %0, %1;" :: "n"(ID), "n"(N) : "memory"); }
__device__ __forceinline__ void gather_item(int i, int cta, uint32_t buf, uint32_t xbar, const CUtensorMap* mZ2) {
  mbar_expect_tx(xbar + i * 8, 4096);
  tma_load_3d(buf + i * 4096, mZ2, xbar + i * 8, cta * 16, (i & 1) * 8, (i >> 1) * 16);
}

__device__ __forceinline__ void cp_wait() { asm volatile("cp.async.wait_all;" ::: "memory"); }
__device__ __forceinline__ void stage4k(uint32_t dst, const void* src, uint32_t bar, int lane) {
  __syncwarp();
  if (lane == 0) { mbar_expect_tx(bar, 4096); bulk_load(dst, src, 4096, bar); }
}

__device__ __forceinline__ void fft_engine(int ph, int cta, int w, int lane, uint32_t buf, uint32_t tw256,
                                           const uint2* __restrict__ Z1, uint2* __restrict__ Z2, const CUtensorMap* mWf,
                                           const CUtensorMap* mZ1, const CUtensorMap* mZ2, uint32_t xbar,
                                           const uint32_t* wmaxp, const uint32_t* lateA, const uint32_t* lateB) {
  h2 r[16], im[16], tc[16], ts[16];
#pragma unroll
  for (int i = 0; i < 16; i++) { r[i] = u2h(0); im[i] = u2h(0); }
  int mode = ph == 0 ? 0 : (ph == 1 ? 4 : 2);
  int it = ph == 1 ? 0 : 2 * w, s = ph == 1 ? (int)wexp_from_max(ldg32(wmaxp)) : 0;
  int unit = b_unit(cta, w, 0), rep = 0;
  const uint32_t scr = buf + w * 8192, stg = scr + 4096, park = buf + 24576 + lane * 8;
  const uint32_t sbar = xbar + 64 + w * 8;
  uint32_t spar = 0;
  if (ph == 1) {
    stage4k(stg, Z1 + unit * 512, sbar, lane);
    if (w == 0) {
      const uint32_t offm = mirror_off(cta, lane);
#pragma unroll
      for (int a = 0; a < 16; a++) asm volatile("cp.async.ca.shared.global [%0], [%1], 8;" :: "r"(park + a * 256), "l"(Z1 + offm + a * 32) : "memory");
      cp_wait();
      mbar_wait(sbar, 0);
_Pragma("unroll 4")
      for (int a = 0; a < 16; a++) {
        h2 pr, pi, mr, mi, c4, s4;
        lds64(stg + a * 256 + lane * 8, pr, pi);
        lds64(park + a * 256, mr, mi);
        lds64(tw256 + 64 + (lane >> 2) * 8 + a * 128, c4, s4);
        h2 x = __hadd2(pi, mi), y = __hsub2(mr, pr);
        cmul_cs(x, y, c4, s4);
        sts64(park + a * 256, x, y);
        sts64(stg + a * 256 + lane * 8, __hadd2(pr, mr), __hsub2(pi, mi));
      }
    }
  }
  {
    const uint32_t twa = tw256 + (ph == 1 ? (lane >> 2) : (lane >> 1)) * 8;
    tc[0] = u2h(ph == 2 ? 0x28002800u : 0x30003000u); ts[0] = tc[0];
#pragma unroll
    for (int c = 1; c < 16; c++) lds64(twa + c * 128, tc[c], ts[c]);
  }
#pragma unroll 1
  for (;;) {
    mode = __popc(__ballot_sync(0xffffffff, lane < mode));
    uint32_t pa = 0;
    if (mode == 0 || mode == 3) {
      pa = buf + (it >> 1) * 8192 + (lane >> 1) * 256 + (swz(lane >> 1) ^ ((it & 1) << 4)) + ((lane & 1) << 3);
#pragma unroll
      for (int a = 0; a < 8; a++) { const uint32_t q = pa ^ swz(a); lds64(q, r[a], im[a]); lds64(q + 4096, r[a+8], im[a+8]); }
    } else if (mode < 3) {
      pa = buf + it * 4096 + (swz(lane >> 2) ^ ((lane & 3) << 3));
      if (mode == 1) {
#pragma unroll
        for (int b = 0; b < 8; b++) { const uint32_t q = (pa ^ swz(b)) + b * 256; lds64(q, r[b], im[b]); lds64(q + 2048, r[b+8], im[b+8]); }
      }
    }
    if (mode == 2 || mode == 4) {
      if (mode == 2) {
        mbar_wait(xbar + it * 8, 0);
        if (lane == 0 && s == 0) gather_item(it + 1, cta, buf, xbar, mZ2);
      } else if (rep == 0) { mbar_wait(sbar, spar); spar ^= 1; }
      const uint32_t pl = mode == 2 ? buf + it * 4096 + lane * 8 : (rep ? park : stg + lane * 8);
#pragma unroll
      for (int d = 0; d < 16; d++) lds64(pl + d * 256, r[d], im[d]);
      if (mode == 4 && rep == 0) {
        fence_proxy_async_smem();
        __syncwarp();
        if (lane == 0) { mbar_expect_tx(sbar, 4096); tma_load_2d(stg, mWf, sbar, (w == 0 ? unit : (unit & 127)) * 32, w == 0 ? 384 : ((unit - 256) >> 7) * 64); }
      }
    }
    if (mode == 0 || mode >= 3) {
      if (mode != 3) fft16(r, im);
      r[0] = __hmul2(r[0], tc[0]); im[0] = __hmul2(im[0], tc[0]);
#pragma unroll
      for (int c = 1; c < 16; c++) cmul_cs(r[c], im[c], tc[c], ts[c]);
      if (mode >= 4) {
        const int me = lane >> 2;
        const uint32_t w0 = scr + lane * 16, w1 = w0 ^ 64;
#pragma unroll
        for (int g = 0; g < 8; g++) {
          const uint32_t rl = __byte_perm(h2u(r[g]), h2u(r[g+8]), 0x5410), rh = __byte_perm(h2u(r[g]), h2u(r[g+8]), 0x7632);
          const uint32_t il = __byte_perm(h2u(im[g]), h2u(im[g+8]), 0x5410), ih = __byte_perm(h2u(im[g]), h2u(im[g+8]), 0x7632);
          sts128(((g & 1) ? w1 : w0) + g * 512, rl, il, rh, ih);
        }
        __syncwarp();
        const uint32_t r0 = scr + me * 512 + (lane & 3) * 16 + (me & 1) * 64, r1 = r0 ^ 64;
#pragma unroll
        for (int g = 0; g < 8; g++) lds128(((g & 1) ? r1 : r0) + (g >> 1) * 128, r[g], im[g], r[g+8], im[g+8]);
      }
    }
    if (mode != 0) fft16(r, im);
    if (mode == 1 || (mode == 5 && w == 0)) {
      __syncwarp();
      const uint32_t pl = mode == 1 ? buf + it * 4096 + lane * 8 : (rep ? park : park + 4096);
#pragma unroll
      for (int d = 0; d < 16; d++) sts64(pl + d * 256, r[d], im[d]);
    }
    if (mode < 4) {
      if (mode == 0 || mode == 3) {
#pragma unroll
        for (int c = 0; c < 8; c++) { const uint32_t q = pa ^ swz(c); sts64(q, r[c], im[c]); sts64(q + 4096, r[c+8], im[c+8]); }
      } else if (mode == 2) {
        __syncwarp();
#pragma unroll
        for (int b = 0; b < 8; b++) { const uint32_t q = (pa ^ swz(b)) + b * 256; sts64(q, r[b], im[b]); sts64(q + 2048, r[b+8], im[b+8]); }
      } else {
        fence_proxy_async_smem();
        __syncwarp();
        if (lane == 0) { tma_store_3d(mZ1, buf + it * 4096, cta * 16, (it & 1) * 8, (it >> 1) * 16); asm volatile("cp.async.bulk.commit_group;" ::: "memory"); }
      }
      s++;
      if (s == 6 || (s == 4 && w == 2)) break;
      if (s == 1 && mode == 0 && w < 2) nb_arrive<11, 96>();
      if (s == 5) {
        if (mode == 0) {
          if (lane == 0) asm volatile("cp.async.bulk.wait_group 0;" ::: "memory");
          __syncwarp();
          nb_arrive<7, 96>();
        }
        nb_sync<6, 64>();
      } else if (s >= 3 && mode == 3 && w < 2 && lane == 0 && rep == 0) {
        if (s == 4) poll_cnt(lateB, 128);
        if (s == 4 || ld_acquire(lateB) >= 128) {
          fence_proxy_async_global();
          gather_item(6 + w, cta, buf, xbar, mZ2);
          rep = 1;
        }
      }
      __syncwarp();
      mode = (mode & 2) + (s < 4 ? (s >> 1) : (s & 1));
      it = s < 4 ? 2 * w + (s & 1) : 6 + w;
    } else if (mode == 4) {
      mbar_wait(sbar, spar); spar ^= 1;
      const bool big = s > 136;
      const uint32_t wmul = (uint32_t)((w == 0 ? 137 : 139) + (big ? 96 : 0) - s) * 0x00800080u;
      if (big) {
#pragma unroll 1
        for (int m = 0; m < 8; m++) {
          h2 t[4]; lds128(stg + m * 512 + lane * 16, t[0], t[1], t[2], t[3]);
          sts128(stg + m * 512 + lane * 16, hmul2_bf16(h2u(t[0]), 0x0f800f80u), hmul2_bf16(h2u(t[1]), 0x0f800f80u), hmul2_bf16(h2u(t[2]), 0x0f800f80u), hmul2_bf16(h2u(t[3]), 0x0f800f80u));
        }
      }
#pragma unroll
      for (int m = 0; m < 8; m++) {
        h2 wv[4]; lds128(stg + m * 512 + lane * 16, wv[0], wv[1], wv[2], wv[3]);
#pragma unroll
        for (int e = 0; e < 4; e++) {
          const uint32_t t = hmul2_bf16(h2u(wv[e]), wmul);
          wv[e] = u2h(t * 8u - (t & 0x80008000u) * 7u);
        }
#pragma unroll
        for (int e = 0; e < 2; e++) {
          const h2 zr = r[2*m+e], zi = im[2*m+e];
          const h2 t = __hmul2(zi, wv[2*e]), u = __hmul2(zr, wv[2*e]);
          r[2*m+e] = __hfma2(zr, wv[2*e+1], t);
          im[2*m+e] = __hfma2(zi, __hneg2(wv[2*e+1]), u);
        }
      }
      fence_proxy_async_smem();
      __syncwarp();
      if (lane == 0 && (w == 0 ? rep == 0 : it < 2)) {
        mbar_expect_tx(sbar, 4096);
        if (w == 0) tma_load_2d(stg, mWf, sbar, unit * 32, 448);
        else {
          if (it == 1) { poll_cnt(lateA, 128); fence_proxy_async_global(); }
          bulk_load(stg, Z1 + b_unit(cta, w, it + 1) * 512, 4096, sbar);
        }
      }
      mode = 5;
    } else {
      uint2* dst = Z2 + unit * 512 + lane;
      mode = 4;
      if (w != 0) {
#pragma unroll
        for (int a = 0; a < 16; a++) dst[a * 32] = make_uint2(h2u(r[a]), h2u(im[a]));
        if (++it == 3) break;
        if (it == 2) nb_arrive<7, 96>();
        unit = b_unit(cta, w, it);
      } else if (rep == 0) {
        rep = 1;
      } else {
        uint2* dm = Z2 + mirror_off(cta, opaque(lane));
        if (unit != 128 || (lane & 3) == 0) {
_Pragma("unroll 4")
          for (int a = 0; a < 16; a++) {
            h2 x, y, p, q, c4, s4;
            lds64(park + 4096 + a * 256, x, y);
            lds64(park + a * 256, p, q);
            lds64(tw256 + 64 + (lane >> 2) * 8 + a * 128, c4, s4);
            cmul_cs(p, q, c4, s4);
            dm[a * 32] = make_uint2(h2u(__hsub2(q, x)), h2u(__hadd2(y, p)));
            dst[a * 32] = make_uint2(h2u(__hadd2(x, q)), h2u(__hsub2(y, p)));
          }
        }
        break;
      }
    }
  }
}

__device__ __forceinline__ uint32_t absmax2(uint32_t a, uint32_t b) { uint32_t r; asm("max.xorsign.abs.bf16x2 %0, %1, %2;" : "=r"(r) : "r"(a), "r"(b)); return r; }
__device__ __forceinline__ uint32_t ldg_nc16(const unsigned short* p) { unsigned short v; asm volatile("ld.global.nc.u16 %0, [%1];" : "=h"(v) : "l"(p)); return v; }
__device__ __forceinline__ uint32_t wprep_item(int I, int lane, const unsigned short* __restrict__ wr, const unsigned short* __restrict__ wi,
                                               uint4* __restrict__ Wf, uint32_t mx) {
  const int U = I >> 2, set = U >> 6, g = U & 63;
  const bool special = set >= 6, mir = !special && (set & 1);
  const int pb = (special ? (set - 6) * 4 : 1 + (set >> 1)) + 8 * ((g & 7) + 32 * (g >> 3));
  const int c0 = (I & 3) * 128 + lane + (mir ? 1 : 0);
  const int idx = (mir ? 2048 - pb : pb) * 513 + c0, dk = mir ? -64 * 513 : 64 * 513;
  uint32_t v[4][8];
#pragma unroll
  for (int k = 0; k < 4; k++)
#pragma unroll
    for (int i = 0; i < 4; i++) { v[i][k] = ldg_nc16(wr + idx + k * dk + 32 * i); v[i][4+k] = ldg_nc16(wi + idx + k * dk + 32 * i); }
  const int ex = lane >> 3;
  if ((I & 3) == 0 && (ex == 0 || (ex == 1 && special))) {
    const int ek = lane & 3, eim = (lane >> 2) & 1;
    const int p = pb + 64 * ek, q = (mir || ex) ? 512 : 0;
    const unsigned short* src = eim ? wi : wr;
    const uint32_t a = ldg_nc16(src + p * 513 + q), b = ldg_nc16(src + ((2048 - p) & 2047) * 513 + q);
    mx = absmax2(mx, a | (b << 16));
    const uint32_t ed = pack_bf16(0.5f * __uint_as_float(a << 16) + (eim ? -0.5f : 0.5f) * __uint_as_float(b << 16), 0.f);
    reinterpret_cast<unsigned short*>(Wf + U * WROW + ex * 512)[(ek >> 1) * 4 + (ek & 1) + eim * 2] = (unsigned short)ed;
  }
  const uint32_t neg = mir ? 0x80008000u : 0u;
  uint4* d = Wf + U * WROW + (mir ? 512 - c0 : c0);
#pragma unroll
  for (int i = 0; i < 4; i++) {
    const uint32_t a = __byte_perm(v[i][0], v[i][1], 0x5410), b = __byte_perm(v[i][4], v[i][5], 0x5410);
    const uint32_t c = __byte_perm(v[i][2], v[i][3], 0x5410), e = __byte_perm(v[i][6], v[i][7], 0x5410);
    mx = absmax2(absmax2(mx, absmax2(a, b)), absmax2(c, e));
    if (((c0 + 32 * i) & 511) != 0) stg128(d + (mir ? -32 * i : 32 * i), a, b ^ neg, c, e ^ neg);
  }
  return mx;
}
__device__ __align__(1024) __nv_bfloat16 g_xn[2048 * 1024];
__device__ __align__(1024) __nv_bfloat16 g_h[2048 * 3584];
__device__ __align__(1024) uint2 g_Z1[ZWORDS];
#define g_Z2 g_Z1
__device__ __align__(1024) uint4 g_Wf[512 * WROW];
#define g_s reinterpret_cast<uint32_t*>(g_Wf)
#define PART(c) (reinterpret_cast<uint4*>(g_xn) + (((c) & 15) * 8 + ((c) >> 4)) * 2048)
__device__ __align__(128) uint32_t g_flag[128 * 32];
__device__ __align__(1024) float2 g_stats[2048];
__device__ __align__(1024) float g_cs[2048];
enum { C_H = 0, C_LN = 64, C_WMAX, C_AW, C_A2, C_B, C_B2, C_C, C_DONE, C_N };
__device__ __align__(128) uint32_t g_cnt[C_N * 32];
#define X_IT 3
#define W_PF 5
#define W_NI 10
#define LA0 3
#define LA1 5
#define LB0 6
#define LB1 7
#define LC0 LB0
#define LC1 LB1
#define LN_IT 16
#define PROM CU_TENSOR_MAP_L2_PROMOTION_L2_128B
#define PA 0
#define PW 2
#define PX 2
#define PUBG 10
#define SEND_IT 84
#define EARLY 1
constexpr int STAGE_BYTES = 49152, A_BYTES = 16384;
constexpr uint32_t OFF_SIDE = 4 * STAGE_BYTES, OFF_CS = OFF_SIDE + 32768, OFF_TW = OFF_CS + 1024 - 128, OFF_BAR = OFF_TW + 2048;
constexpr uint32_t OFF_XT = OFF_SIDE, OFF_SEND = A_BYTES + 16384, OFF_RECV = OFF_SEND + 2 * STAGE_BYTES;
constexpr int SMEM_BYTES = OFF_BAR + 128;
constexpr uint32_t B_FULL = 0, B_EMPTY = 32, B_SEND = 64, B_RECV = 72, B_LN = 80, B_XF = 88, B_SR = 96, B_HS = 104, B_CS = 112, B_E0 = 120;
constexpr int N_DONE = 128 * (1 + NSIDE) + 1;

__device__ __forceinline__ void finish_role() {
  uint32_t old = atomicAdd(&g_cnt[C_DONE * 32], 1u);
  if (old == N_DONE - 1) {
#pragma unroll 1
    for (int i = 0; i < C_N; i++) *reinterpret_cast<uint2*>(&g_cnt[i * 32]) = make_uint2(0, 0);
  }
}
__device__ __forceinline__ void epi_half(const float (&a)[64], uint32_t* h0, uint32_t* h1) {
#pragma unroll
  for (int j = 0; j < 8; j++) {
    const int b = j * 4;
    h0[j] = hmul2_bf16(pack_bf16(silu_half(a[b]), silu_half(a[b+1])), pack_bf16(a[b+32], a[b+33]));
    h1[j] = hmul2_bf16(pack_bf16(silu_half(a[b+2]), silu_half(a[b+3])), pack_bf16(a[b+34], a[b+35]));
  }
}
__device__ __forceinline__ void pack_half(const float (&a)[64], uint32_t (&p)[32]) {
#pragma unroll
  for (int j = 0; j < 32; j++) p[j] = pack_bf16(a[2*j], a[2*j+1]);
}
__device__ __forceinline__ uint32_t glu_packed(uint32_t g, uint32_t u) { return hmul2_bf16(pack_bf16(silu_half(bf_lo(g)), silu_half(bf_hi(g))), u); }
__device__ __forceinline__ void ln_fix(float (&a)[64], uint32_t cp, float r0, float m0, float r1, float m1) {
#pragma unroll
  for (int j = 0; j < 16; j++) {
    float c0, c1;
    asm volatile("ld.shared.v2.f32 {%0,%1}, [%2];" : "=f"(c0), "=f"(c1) : "r"(cp + j * 32));
    a[j*4] = fmaf(m0, c0, a[j*4]) * r0; a[j*4+1] = fmaf(m0, c1, a[j*4+1]) * r0;
    a[j*4+2] = fmaf(m1, c0, a[j*4+2]) * r1; a[j*4+3] = fmaf(m1, c1, a[j*4+3]) * r1;
  }
}
template<int ST, int HALF> __device__ __forceinline__ void mma_half(float (&a)[64], uint32_t da, uint32_t db) {
  constexpr int O = ST * (STAGE_BYTES / 16);
  wgmma_k64_n128<O, O + HALF * 1024, 1>(a, da, db);
  wgmma_commit();
}
template<int ST, int FIRST, int WAIT = 1> __device__ __forceinline__ void mma_step(float (&a)[128], uint32_t da, uint32_t db, uint32_t fullb, uint32_t par) {
  constexpr int O = ST * (STAGE_BYTES / 16);
  if (WAIT) mbar_wait(fullb + 8 * ST, par);
  wgmma_fence();
  wgmma_k64_n256<O, O, !FIRST>(a, da, db);
  wgmma_commit();
}

__global__ void __cluster_dims__(2, 1, 1) __launch_bounds__(384, 1)
fused_kernel(const __grid_constant__ CUtensorMap mXn, const __grid_constant__ CUtensorMap mH,
             const __grid_constant__ CUtensorMap mWg, const __grid_constant__ CUtensorMap mWu,
             const __grid_constant__ CUtensorMap mWd, const __grid_constant__ CUtensorMap mX,
             const __grid_constant__ CUtensorMap mOut, const __grid_constant__ CUtensorMap mZ1,
             const __grid_constant__ CUtensorMap mZ2, const __grid_constant__ CUtensorMap mWf,
             const __nv_bfloat16* __restrict__ x, const unsigned short* __restrict__ wr, const unsigned short* __restrict__ wi,
             const __nv_bfloat16* __restrict__ wg, const __nv_bfloat16* __restrict__ wu) {
  extern __shared__ __align__(1024) uint8_t smem_raw[];
  const uint32_t sbase = smem_u32(smem_raw);
  const uint32_t bars = sbase + OFF_BAR;
  const int tid = threadIdx.x;
  const int warp_id = __shfl_sync(0xffffffff, tid >> 5, 0);
  if (blockIdx.x >= 128) {
    uint32_t mx = 0;
#pragma unroll 1
    for (int I = 128 * W_NI + (blockIdx.x - 128) * 12 + warp_id; I < 2048; I += 48) mx = wprep_item(I, tid & 31, wr, wi, g_Wf, mx);
    mx = __reduce_max_sync(0xffffffff, max(mx & 0x7fffu, (mx >> 16) & 0x7fffu));
    if ((tid & 31) == 0) atomicMax(&g_cnt[C_WMAX * 32], mx);
    __syncthreads();
    if (tid == 0) { red_release(&g_cnt[C_AW * 32], 1); }
    if (blockIdx.x != 128 || warp_id >= 4) return;
  } else {
    if (tid == 0) {
      for (int s = 0; s < 4; s++) { mbar_init(bars + B_FULL + 8 * s, 1); mbar_init(bars + B_EMPTY + 8 * s, 4); }
      mbar_init(bars + B_SEND, 9); mbar_init(bars + B_RECV, 1); mbar_init(bars + B_LN, 8 + NSIDE);
      mbar_init(bars + B_XF, 1); mbar_init(bars + B_SR, 1);
      asm volatile("st.shared.u32 [%0], %1;" :: "r"(bars + B_HS), "r"(0u) : "memory"); mbar_init(bars + B_CS, 1); mbar_init(bars + B_E0, 8);
      asm volatile("fence.mbarrier_init.release.cluster;" ::: "memory");
    }
    __syncthreads();
    asm volatile("barrier.cluster.arrive.relaxed.aligned;" ::: "memory");
    if (tid == 0) {
      fence_proxy_async_smem();
#pragma unroll 1
      for (int s = 0; s < EARLY; s++) {
        const uint32_t sa = sbase + s * STAGE_BYTES, fb = bars + B_FULL + 8 * s;
        const int n0 = (blockIdx.x >> 4) * 128;
        mbar_expect_tx(fb, STAGE_BYTES);
        tma_load_2d(sa, &mX, fb, s * 64, (blockIdx.x & 15) * 128);
        tma_load_2d(sa + A_BYTES, &mWg, fb, n0, s * 64);
        tma_load_2d(sa + A_BYTES + 8192, &mWu, fb, n0, s * 64);
        tma_load_2d(sa + A_BYTES + 16384, &mWg, fb, n0 + 64, s * 64);
        tma_load_2d(sa + A_BYTES + 24576, &mWu, fb, n0 + 64, s * 64);
      }
    }
    __syncwarp();
    asm volatile("barrier.cluster.wait.acquire.aligned;" ::: "memory");
  }

  if (warp_id < 4) {
    reg_dec<120>();
    if (warp_id == 0) {
     if (tid == 0 && blockIdx.x < 128) {
      const int rank = blockIdx.x & 1, cl = blockIdx.x >> 1;
      const int mb = (cl & 7) * 2 + rank, j8 = cl >> 3, type = j8 & 1, grp = j8 >> 1;
      const int n_g1 = type == 0 ? 64 : 48;
      const int cw = grp * 256 + (type ^ rank) * 128;
#pragma unroll 1
      for (int it = EARLY; it < 86; it++) {
        const int st = it & 3, t = it >> 4;
        const uint32_t sa = sbase + st * STAGE_BYTES, sb = sa + A_BYTES + rank * 16384, fb = bars + B_FULL + 8 * st;
        if (it == LN_IT) {
          poll_cnt(&g_cnt[C_LN * 32], 128);
          fence_proxy_async_global();
          mbar_expect_tx(bars + B_CS, 1024);
          bulk_load(sbase + OFF_CS, g_cs + j8 * 256, 1024, bars + B_CS);
        }
        if (it < n_g1) {
          const int kb = it & 15, n0 = (t < 3 ? t * 8 + j8 : 24 + grp) * 128 + rank * 64;
          mbar_wait(bars + B_EMPTY + 8 * st, ((it >> 2) & 1) ^ 1);
          mbar_expect_tx(fb, STAGE_BYTES);
          tma_load_2d(sa, t == 0 ? &mX : &mXn, fb, kb * 64, mb * 128);
          tma_load_2d_mc(sb, &mWg, fb, n0, kb * 64);
          tma_load_2d_mc(sb + 8192, &mWu, fb, n0, kb * 64);
          if (it == X_IT) {
            mbar_expect_tx(bars + B_XF, 32768);
            const __nv_bfloat16* px = x + ((blockIdx.x >> 3) * 16 + (blockIdx.x & 7)) * 1024;
#pragma unroll 1
            for (int r = 0; r < 16; r++) bulk_load(sbase + OFF_SIDE + r * 2048, px + ((r >> 1) * 256 + (r & 1) * 8) * 1024, 2048, bars + B_XF);
          }
          if (it == W_PF) {
            asm volatile("cp.async.bulk.prefetch.L2.global [%0], 16416;" :: "l"(wr + blockIdx.x * 8208) : "memory");
            asm volatile("cp.async.bulk.prefetch.L2.global [%0], 16416;" :: "l"(wi + blockIdx.x * 8208) : "memory");
          }
          if (it == 3) { prefetch_tmap(&mXn); prefetch_tmap(&mH); prefetch_tmap(&mWd); prefetch_tmap(&mOut); }
        } else {
          const int kb = it < 64 ? it - 48 : (it < 80 ? it - 48 + (it & 8) + type * 8 : (it < 82 ? it - 32 + type * 2 : it - 30));
          if ((it & 7) == 0 && it != 56) {
            const int wave = kb >> 4;
            poll_cnt(&g_cnt[(C_H + mb * 4 + wave) * 32], wave < 3 ? 8 : 4);
            fence_proxy_async_global();
          }
          mbar_wait(bars + B_EMPTY + 8 * st, ((it >> 2) & 1) ^ 1);
          mbar_expect_tx(fb, it < 82 ? STAGE_BYTES : 32768);
          tma_load_2d(sa, &mH, fb, 0, (mb * 56 + kb) * 128);
          if (it < 82) {
            tma_load_5d_mc(sb, &mWd, fb, cw, kb * 2);
            tma_load_5d_mc(sb + 8192, &mWd, fb, cw + 64, kb * 2);
          } else tma_load_5d_mc(sa + A_BYTES + rank * 8192, &mWd, fb, j8 * 128 + rank * 64, kb * 2);
          if (it == SEND_IT) {
            mbar_wait(bars + B_SEND, 0);
            asm volatile("cp.async.bulk.global.shared::cta.bulk_group [%0], [%1], 16384;" :: "l"(PART(blockIdx.x)), "r"(sbase + OFF_SEND) : "memory");
            asm volatile("cp.async.bulk.global.shared::cta.bulk_group [%0], [%1], 16384;" :: "l"(PART(blockIdx.x) + 1024), "r"(sbase + OFF_SEND + STAGE_BYTES) : "memory");
            asm volatile("cp.async.bulk.commit_group;" ::: "memory");
          }
          if (it == 78) poll_cnt(&g_cnt[C_B * 32], 129);
        }
      }
      mbar_expect_tx(bars + B_RECV, 32768);
      asm volatile("cp.async.bulk.wait_group 0;" ::: "memory");
      asm volatile("st.release.gpu.global.u32 [%0], %1;" :: "l"(g_flag + blockIdx.x * 32), "r"(1u) : "memory");
      { uint32_t n = 0; while (ld_acquire(&g_flag[(blockIdx.x ^ 16) * 32]) == 0 && ++n < (1u << 20)) {} }
      fence_proxy_async_global();
      bulk_load(sbase + OFF_RECV, PART(blockIdx.x ^ 16), 16384, bars + B_RECV);
      bulk_load(sbase + OFF_RECV + STAGE_BYTES, PART(blockIdx.x ^ 16) + 1024, 16384, bars + B_RECV);
      finish_role();
     }
    } else {
    const int cta = blockIdx.x;
    const uint32_t buf = sbase + OFF_SIDE;
    const uint32_t tw256 = sbase + OFF_TW;
#pragma unroll 1
    for (int ph = cta < 128 ? 0 : 1; ; ph++) {
      const int st = opaque(threadIdx.x) - 32, lane = st & 31, w = __shfl_sync(0xffffffff, st >> 5, 0);
      ph = __shfl_sync(0xffffffff, ph, 0);
      if (ph == 0) {
        build_tw256(st, 96, tw256, 0.125f);
        mbar_wait(bars + B_FULL, 0);
        colsum64(cta, w, lane, wg, wu, g_cs);
        __syncwarp();
        if (lane == 0) mbar_arrive(bars + B_LN);
        if (w == 2) {
          mbar_wait(bars + B_LN, 0);
          if (lane == 0) { red_release(&g_cnt[C_LN * 32], 1); }
          __syncwarp();
        }
        {
          uint32_t mx = 0;
#pragma unroll 1
          for (int I = w * 4; I < min(w * 4 + 4, W_NI); I++) mx = wprep_item(cta * W_NI + I, lane, wr, wi, g_Wf, mx);
          mx = __reduce_max_sync(0xffffffff, max(mx & 0x7fffu, (mx >> 16) & 0x7fffu));
          if (lane == 0) atomicMax(&g_cnt[C_WMAX * 32], mx);
        }
        mbar_wait(bars + B_LN, 0);
        pass_a0(cta, w, lane, buf);
        side_bar();
      } else if (ph == 1) {
        const bool reg = cta < 128;
        if (lane == 0) asm volatile("cp.async.bulk.wait_group 0;" ::: "memory");
        __syncwarp();
        if (w == 2) {
          if (reg) {
            mbar_wait(bars + B_E0, 0);
            nb_sync<11, 96>();
          }
          if (lane < 11) { mbar_init(sbase + OFF_CS + lane * 8, 1); fence_proxy_async_smem(); }
          build_tb(lane, tw256);
          __syncwarp();
          nb_arrive<9, 64>();
          if (!reg) return;
          nb_arrive<10, 64>();
          nb_sync<7, 96>();
          if (lane == 0) {
            smem_wait(bars + B_HS, 8);
            red_release(&g_cnt[C_AW * 32], 1);
            atomicAdd(&g_cnt[(C_H + (cta & 15) * 4) * 32], 1u);
          }
          __syncwarp();
        } else if (w == 1) {
          if (!reg) return;
          nb_arrive<8, 64>();
          nb_sync<10, 64>();
        } else {
          if (reg) {
            nb_sync<8, 64>();
            if (lane == 0) red_release(&g_cnt[C_A2 * 32], 1);
            __syncwarp();
          }
          nb_sync<9, 64>();
        }
        if (lane == 0) { poll_cnt(&g_cnt[C_AW * 32], 132); fence_proxy_async_global(); }
        __syncwarp();
      } else if (ph == 2) {
        __syncwarp();
        if (cta >= 128) { if (lane == 0) { red_release(&g_cnt[C_B * 32], 1); finish_role(); } return; }
        if (w == 0) {
          if (lane < 2) reinterpret_cast<uint4*>(g_flag + cta * 32)[lane] = make_uint4(0, 0, 0, 0);
          nb_sync<7, 96>();
          if (lane == 0) {
            smem_wait(bars + B_HS, 24);
            red_release(&g_cnt[C_B * 32], 1);
            atomicAdd(&g_cnt[(C_H + (cta & 15) * 4 + 2) * 32], 1u);
            mbar_arrive(bars + B_SEND);
          }
          __syncwarp();
          build_tw256(lane, 32, tw256, 0.03125f);
          if (lane < 4) reinterpret_cast<float4*>(g_cs)[cta * 4 + lane] = make_float4(0.f, 0.f, 0.f, 0.f);
          __syncwarp();
          nb_arrive<9, 64>();
          nb_arrive<10, 64>();
        } else if (w == 1) {
          nb_arrive<8, 64>();
          nb_sync<9, 64>();
        } else {
          nb_sync<8, 64>();
          if (lane == 0) red_release(&g_cnt[C_B2 * 32], 1);
          __syncwarp();
          nb_sync<10, 64>();
        }
        fence_proxy_async_smem();
        __syncwarp();
        if (lane == 0) {
          poll_cnt(&g_cnt[C_B * 32], 129);
          fence_proxy_async_global();
          gather_item(2 * w, cta, buf, sbase + OFF_CS, &mZ2);
        }
        __syncwarp();
      } else {
        if (w == 2) {
          const __nv_bfloat16* px = x + ((cta & 15) * 128 + (lane >> 1)) * 1024 + (cta >> 4) * 128 + (lane & 1) * 64;
#pragma unroll
          for (int i = 0; i < 8; i++) asm volatile("prefetch.global.L2 [%0];" :: "l"(px + i * 16 * 1024));
        }
        if (st == 64 && !(cta & 16)) { smem_wait(bars + B_HS, 32); red_release(&g_cnt[(C_H + (cta & 15) * 4 + 3) * 32], 1); }
        side_bar();
        pass_c0(cta, w, lane, buf, g_s);
        break;
      }
      fft_engine(ph, cta, w, lane, buf, tw256, g_Z1, g_Z2, &mWf, &mZ1, &mZ2, sbase + OFF_CS, &g_cnt[C_WMAX * 32], &g_cnt[C_A2 * 32], &g_cnt[C_B2 * 32]);
    }
    const int st = threadIdx.x - 32, lane = st & 31;
    side_bar();
    if (st == 32) {
      const int cl = cta >> 1, mb = (cl & 7) * 2 + (cta & 1), ck = (cl >> 3) * 128;
      const float fs = __uint_as_float((wexp_from_max(ldg32(&g_cnt[C_WMAX * 32])) - 2) << 23);
      asm volatile("st.shared.f32 [%0], %1;" :: "r"(sbase + OFF_CS + 128), "f"(fs) : "memory");
      red_release(&g_cnt[C_C * 32], 1);
      fence_proxy_async_smem();
      mbar_expect_tx(bars + B_XF, 32768);
      tma_load_2d(sbase + OFF_XT, &mX, bars + B_XF, ck, mb * 128);
      tma_load_2d(sbase + OFF_XT + 16384, &mX, bars + B_XF, ck + 64, mb * 128);
      poll_cnt(&g_cnt[C_C * 32], 128);
      mbar_arrive(bars + B_SR);
    }
    if (lane == 0) finish_role();
    }
  } else {
    reg_inc<192>();
    const int w = (warp_id >> 2) - 1, warp = warp_id & 3, lane = tid & 31;
    const int rank = blockIdx.x & 1, cl = blockIdx.x >> 1;
    const int mb = (cl & 7) * 2 + rank, j8 = cl >> 3, type = j8 & 1, grp = j8 >> 1;
    float acc[128];
    uint32_t hold[32];
    const uint32_t da0 = (((sbase + w * 8192) & 0x3FFFF) >> 4) | (1u << 16);
    const uint32_t db0 = (((sbase + A_BYTES) & 0x3FFFF) >> 4) | (512u << 16);
    const bool rel = (tid & 95) == 0;
    const uint32_t eb = mapa(bars + B_EMPTY, (warp & 1) ^ rank);
#define MMA_STEP(st, par, first) mma_step<st, first>(acc, da0, db0, bars + B_FULL, par)
#define MMA_RELEASE(st) do { wgmma_wait<1>(); if (rel) mbar_arrive_cl(eb + 8 * (((st) + 3) & 3)); } while (0)
    MMA_STEP(0, 0, 1);
    {
      float inv[2] = {0.f, 0.f}; uint32_t mb2[2] = {0u, 0u};
#pragma unroll
      for (int i = 0; i < 32; i++) hold[i] = 0;
#pragma unroll 1
      for (int s = 1; s < 12; s++) {
        const uint32_t so = (s & 3) * (STAGE_BYTES / 16);
        mma_step<0, 0>(acc, da0 + so, db0 + so, bars + B_FULL + (s & 3) * 8, (s >> 2) & 1);
        wgmma_wait<1>();
        if (rel) mbar_arrive_cl(eb + 8 * ((s + 3) & 3));
        const int t2 = opaque(threadIdx.x);
        if (s == (w ? LA1 : LA0)) {
          float piv[2], sm[2], sq[2];
          mbar_wait(bars + B_XF, 0);
          ln_load((t2 >> 5) - 4, t2 & 31, sbase + OFF_SIDE, hold);
          ln_sums(hold, piv, sm, sq);
          ln_stats(blockIdx.x, (t2 >> 5) - 4, t2 & 31, piv, sm, sq, g_stats, inv, mb2);
        } else if (s == (w ? LB1 : LB0)) {
          if (w == 0) asm volatile("bar.sync 4, 128;" ::: "memory"); else asm volatile("bar.sync 5, 128;" ::: "memory");
          ln_apply<0>(blockIdx.x, (t2 >> 5) - 4, t2 & 31, sbase + OFF_SIDE, hold, g_xn, inv, mb2);
        }
        if (s == (w ? LC1 : LC0)) {
          ln_apply<1>(blockIdx.x, (t2 >> 5) - 4, t2 & 31, sbase + OFF_SIDE, hold, g_xn, inv, mb2);
          __syncwarp();
          if ((t2 & 31) == 0) mbar_arrive(bars + B_LN);
        }
      }
    }
    const int ntiles = type == 0 ? 4 : 3;
    int g = 3;
    mbar_wait(bars + B_FULL, 1);
#pragma unroll 1
    for (int t = 0; ; t++) {
      const int gend = t < ntiles ? t * 4 + 4 : 20;
#pragma unroll 1
      for (; g < gend; g++) {
#define NEXT(st, par) do { const bool ok_ = mbar_test(bars + B_FULL + 8 * (((st) + 1) & 3), par); MMA_RELEASE(st); \
                           if (!ok_) mbar_wait_slow(bars + B_FULL + 8 * (((st) + 1) & 3), par); } while (0)
        mma_step<0, 0, 0>(acc, da0, db0, 0, 0); NEXT(0, g & 1);
        mma_step<1, 0, 0>(acc, da0, db0, 0, 0); NEXT(1, g & 1);
        mma_step<2, 0, 0>(acc, da0, db0, 0, 0);
        if (g == PUBG) {
          if (opaque(threadIdx.x) == 352) { smem_wait(bars + B_HS, 16); red_release(&g_cnt[(C_H + mb * 4 + 1) * 32], 1); }
          __syncwarp();
        }
        NEXT(2, g & 1);
        mma_step<3, 0, 0>(acc, da0, db0, 0, 0); NEXT(3, (g + 1) & 1);
      }
      if (t == ntiles) break;
      const int t2 = opaque(threadIdx.x);
      uint2 s0 = make_uint2(0, 0), s1 = s0;
      if (t == 0) {
        mbar_wait(bars + B_CS, 0);
        const uint2* pst = reinterpret_cast<const uint2*>(g_stats) + mb * 128 + ((t2 - 128) >> 5) * 16 + ((t2 & 31) >> 2);
        s0 = ldg64(pst); s1 = ldg64(pst + 8);
      }
      wgmma_wait<0>();
      if (rel) mbar_arrive_cl(eb + 24);
      if (t == 0) {
        const float r0 = __uint_as_float(s0.x), m0 = __uint_as_float(s0.y), r1 = __uint_as_float(s1.x), m1 = __uint_as_float(s1.y);
        const uint32_t cp = sbase + OFF_CS + (t2 & 3) * 8;
        ln_fix(*reinterpret_cast<float(*)[64]>(&acc[0]), cp, r0, m0, r1, m1);
        ln_fix(*reinterpret_cast<float(*)[64]>(&acc[64]), cp + 512, r0, m0, r1, m1);
        __syncwarp();
        if ((t2 & 31) == 0) mbar_arrive(bars + B_E0);
      }
      __nv_bfloat16* ho = g_h + ((mb * 56 + (t < 3 ? t * 8 + j8 : 24 + grp) * 2) * 128 + ((t2 - 128) >> 5) * 16 + ((t2 & 31) >> 2)) * 64 + (t2 & 3) * 8;
      uint32_t e0[8], e1[8];
      epi_half(*reinterpret_cast<float(*)[64]>(&acc[0]), e0, e1);
      pack_half(*reinterpret_cast<float(*)[64]>(&acc[64]), hold);
#pragma unroll
      for (int j = 0; j < 8; j++) asm volatile("" : "+r"(e0[j]), "+r"(e1[j]));
#pragma unroll
      for (int j = 0; j < 32; j++) asm volatile("" : "+r"(hold[j]));
      mma_step<0, 1, 0>(acc, da0, db0, 0, 0);
#pragma unroll
      for (int j = 0; j < 8; j++) { hold[j] = glu_packed(hold[j], hold[16+j]); asm volatile("" : "+r"(hold[j])); }
      MMA_STEP(1, 0, 0);
      stg128(ho, e0[0], e0[1], e0[2], e0[3]); stg128(ho + 512, e1[0], e1[1], e1[2], e1[3]);
      stg128(ho + 32, e0[4], e0[5], e0[6], e0[7]);
#pragma unroll
      for (int j = 8; j < 16; j++) { hold[j] = glu_packed(hold[j], hold[16+j]); asm volatile("" : "+r"(hold[j])); }
      MMA_RELEASE(1);
      MMA_STEP(2, 0, 0);
      stg128(ho + 32 + 512, e1[4], e1[5], e1[6], e1[7]);
      stg128(ho + 8192, hold[0], hold[2], hold[4], hold[6]); stg128(ho + 8192 + 512, hold[1], hold[3], hold[5], hold[7]);
      MMA_RELEASE(2);
      MMA_STEP(3, 0, 0);
      stg128(ho + 8192 + 32, hold[8], hold[10], hold[12], hold[14]); stg128(ho + 8192 + 32 + 512, hold[9], hold[11], hold[13], hold[15]);
      __syncwarp();
      if ((t2 & 31) == 0) asm volatile("red.release.cta.shared.add.u32 [%0], 1;" :: "r"(bars + B_HS) : "memory");
      NEXT(3, 1);
      g++;
    }
    float a0[64], a1[64];
    wgmma_wait<0>();
    if (rel) mbar_arrive_cl(eb + 24);
#pragma unroll
    for (int i = 0; i < 64; i++) { asm volatile("mov.b32 %0, %1;" : "=f"(a0[i]) : "f"(acc[i])); asm volatile("mov.b32 %0, %1;" : "=f"(a1[i]) : "f"(acc[64+i])); }
    wgmma_fence(); mma_half<0, 1>(a1, da0, db0);
    mbar_wait(bars + B_FULL + 8, 0); wgmma_fence(); mma_half<1, 1>(a1, da0, db0);
    mma_half<0, 0>(a0, da0, db0);
    wgmma_wait<1>();
    asm volatile("bar.sync 3, 256;" ::: "memory");
    wgmma_fence(); mma_half<1, 0>(a0, da0, db0);
    const uint32_t toff = w * STAGE_BYTES + (tid & 127) * 16;
#pragma unroll
    for (int i = 0; i < 8; i++)
      sts128(sbase + OFF_SEND + toff + i * 2048, pack_bf16(a1[i*8], a1[i*8+1]), pack_bf16(a1[i*8+2], a1[i*8+3]), pack_bf16(a1[i*8+4], a1[i*8+5]), pack_bf16(a1[i*8+6], a1[i*8+7]));
    MMA_RELEASE(1);
    fence_proxy_async_smem();
    __syncwarp();
    if (lane == 0) mbar_arrive(bars + B_SEND);
    mbar_wait(bars + B_FULL + 16, 0); wgmma_fence(); mma_half<2, 0>(a0, da0, db0);
    MMA_RELEASE(2);
    mbar_wait(bars + B_FULL + 24, 0); wgmma_fence(); mma_half<3, 0>(a0, da0, db0);
    const uint4* ps = reinterpret_cast<const uint4*>(g_s + ((mb * 8 + w * 4 + warp) * 8 + (lane >> 2)) * 1024 + grp * 256 + type * 128) + (lane & 3);
    const bool early = __all_sync(0xffffffff, mbar_test(bars + B_SR, 0));
    if (early) {
#pragma unroll
      for (int i = 0; i < 8; i++) { const uint4 u = ldg128(ps + i * 4); hold[i*4] = u.x; hold[i*4+1] = u.y; hold[i*4+2] = u.z; hold[i*4+3] = u.w; }
    }
    mbar_wait(bars + B_FULL, 1); wgmma_fence(); mma_half<0, 0>(a0, da0, db0);
    mbar_wait(bars + B_FULL + 8, 1); wgmma_fence(); mma_half<1, 0>(a0, da0, db0);
    if (!early) {
      mbar_wait(bars + B_SR, 0);
#pragma unroll
      for (int i = 0; i < 8; i++) { const uint4 u = ldg128(ps + i * 4); hold[i*4] = u.x; hold[i*4+1] = u.y; hold[i*4+2] = u.z; hold[i*4+3] = u.w; }
    }
    float fs;
    asm volatile("ld.shared.f32 %0, [%1];" : "=f"(fs) : "r"(sbase + OFF_CS + 128) : "memory");
    wgmma_wait<0>();
    if (w == 0) asm volatile("bar.sync 4, 128;" ::: "memory"); else asm volatile("bar.sync 5, 128;" ::: "memory");
    const uint32_t sp = sbase + w * 8192 + (tid & 127) * 16;
#pragma unroll
    for (int i = 0; i < 8; i++) {
      const float2 f0 = __half22float2(u2h(hold[4*i])), f1 = __half22float2(u2h(hold[4*i+1])), f2 = __half22float2(u2h(hold[4*i+2])), f3 = __half22float2(u2h(hold[4*i+3]));
      sts128(sp + (i >> 2) * STAGE_BYTES + (i & 3) * 2048, pack_bf16(f0.x * fs, f1.x * fs), pack_bf16(f0.y * fs, f1.y * fs), pack_bf16(f2.x * fs, f3.x * fs), pack_bf16(f2.y * fs, f3.y * fs));
    }
    const int xr = w * 64 + warp * 16 + (lane & 7) + ((lane >> 3) & 1) * 8;
    const uint32_t xa = sbase + OFF_XT + xr * 128;
    mbar_wait(bars + B_XF, 1);
#pragma unroll
    for (int B = 0; B < 8; B++) {
      const uint32_t ad = xa + (B >> 2) * 16384 + ((((B & 3) * 2 + (lane >> 4)) ^ (lane & 7)) << 4);
      asm volatile("ldmatrix.sync.aligned.m8n8.x4.shared.b16 {%0,%1,%2,%3}, [%4];" : "=r"(hold[B*4]), "=r"(hold[B*4+1]), "=r"(hold[B*4+2]), "=r"(hold[B*4+3]) : "r"(ad) : "memory");
    }
    uint32_t sv[32];
#pragma unroll
    for (int i = 0; i < 8; i++)
      asm volatile("ld.shared.v4.b32 {%0,%1,%2,%3}, [%4];" : "=r"(sv[i*4]), "=r"(sv[i*4+1]), "=r"(sv[i*4+2]), "=r"(sv[i*4+3]) : "r"(sp + (i >> 2) * STAGE_BYTES + (i & 3) * 2048) : "memory");
    mbar_wait(bars + B_RECV, 0);
    const int ck = grp * 256 + type * 128;
#pragma unroll
    for (int B = 0; B < 8; B++) {
      uint32_t pv[4], ov[4];
      asm volatile("ld.shared.v4.b32 {%0,%1,%2,%3}, [%4];" : "=r"(pv[0]), "=r"(pv[1]), "=r"(pv[2]), "=r"(pv[3]) : "r"(sbase + OFF_RECV + toff + B * 2048) : "memory");
#pragma unroll
      for (int e = 0; e < 4; e++) {
        const int a = B * 8 + e * 2;
        const uint32_t g2 = pack_bf16(silu_half(a0[a] + bf_lo(pv[e])), silu_half(a0[a+1] + bf_hi(pv[e])));
        asm("fma.rn.bf16x2 %0, %1, %2, %3;" : "=r"(ov[e]) : "r"(sv[B*4+e]), "r"(g2), "r"(hold[B*4+e]));
      }
      const uint32_t ad = xa + (B >> 2) * 16384 + ((((B & 3) * 2 + (lane >> 4)) ^ (lane & 7)) << 4);
      asm volatile("stmatrix.sync.aligned.m8n8.x4.shared.b16 [%0], {%1,%2,%3,%4};" :: "r"(ad), "r"(ov[0]), "r"(ov[1]), "r"(ov[2]), "r"(ov[3]) : "memory");
      if ((B & 3) == 3) {
        fence_proxy_async_smem();
        __syncwarp();
        if (lane == 0) {
          tma_store_2d(&mOut, sbase + OFF_XT + (B >> 2) * 16384 + (w * 64 + warp * 16) * 128, ck + (B >> 2) * 64, mb * 128 + w * 64 + warp * 16);
          asm volatile("cp.async.bulk.commit_group;" ::: "memory");
        }
      }
    }
    if (lane == 0) asm volatile("cp.async.bulk.wait_group.read 0;" ::: "memory");
  }
}

typedef CUresult (*EncodeFn)(CUtensorMap*, CUtensorMapDataType, cuuint32_t, void*, const cuuint64_t*, const cuuint64_t*, const cuuint32_t*, const cuuint32_t*, CUtensorMapInterleave, CUtensorMapSwizzle, CUtensorMapL2promotion, CUtensorMapFloatOOBfill);
static void make_map(EncodeFn enc, CUtensorMap* m, const void* ptr, int rank, const cuuint64_t* dims, const cuuint64_t* strides, const cuuint32_t* box,
                     CUtensorMapSwizzle swz = CU_TENSOR_MAP_SWIZZLE_128B, CUtensorMapL2promotion prom = PROM) {
  cuuint32_t es[5] = {1, 1, 1, 1, 1};
  enc(m, CU_TENSOR_MAP_DATA_TYPE_BFLOAT16, rank, const_cast<void*>(ptr), dims, strides, box, es, CU_TENSOR_MAP_INTERLEAVE_NONE,
      swz, prom, CU_TENSOR_MAP_FLOAT_OOB_FILL_NONE);
}
static void make_map2(EncodeFn enc, CUtensorMap* m, const void* ptr, uint64_t cols, uint64_t rows, uint32_t bc, uint32_t br, int prom) {
  cuuint64_t d[2] = {cols, rows}, s[1] = {cols * 2}; cuuint32_t b[2] = {bc, br};
  make_map(enc, m, ptr, 2, d, s, b, CU_TENSOR_MAP_SWIZZLE_128B, (CUtensorMapL2promotion)prom);
}

extern "C" void kernel_launch(void* const* d_in, const int* in_sizes, int n_in, void* d_out, int out_size) {
  void* fn = nullptr; cudaDriverEntryPointQueryResult q;
  cudaGetDriverEntryPoint("cuTensorMapEncodeTiled", &fn, cudaEnableDefault, &q);
  EncodeFn enc = (EncodeFn)fn;
  void *pxn, *ph, *pz1, *pz2, *pwf;
  cudaGetSymbolAddress(&pz1, g_Z1); cudaGetSymbolAddress(&pz2, g_Z2); cudaGetSymbolAddress(&pwf, g_Wf);
  cudaGetSymbolAddress(&pxn, g_xn); cudaGetSymbolAddress(&ph, g_h);
  CUtensorMap mXn, mH, mWg, mWu, mWd, mX, mOut, mZ1, mZ2, mWf;
  make_map2(enc, &mXn, pxn, 1024, 2048, 64, 128, PA);
  make_map2(enc, &mH, ph, 64, 2048 * 56, 64, 128, PA);
  make_map2(enc, &mWg, d_in[4], 3584, 1024, 64, 64, PW);
  make_map2(enc, &mWu, d_in[5], 3584, 1024, 64, 64, PW);
  {
    cuuint64_t d[5] = {1024, 2, 4, 4, 112}, s[4] = {2048, 8 * 2048, 2 * 2048, 32 * 2048}; cuuint32_t b[5] = {64, 2, 4, 4, 2};
    make_map(enc, &mWd, d_in[6], 5, d, s, b, CU_TENSOR_MAP_SWIZZLE_128B, (CUtensorMapL2promotion)PW);
  }
  make_map2(enc, &mX, d_in[0], 1024, 2048, 64, 128, PX);
  make_map2(enc, &mOut, d_out, 1024, 2048, 64, 16, 0);
  {
    cuuint64_t d[3] = {2048, 16, 64}, s[2] = {4096, 65536}; cuuint32_t b[3] = {16, 8, 16};
    make_map(enc, &mZ1, pz1, 3, d, s, b, CU_TENSOR_MAP_SWIZZLE_NONE, CU_TENSOR_MAP_L2_PROMOTION_NONE);
    make_map(enc, &mZ2, pz2, 3, d, s, b, CU_TENSOR_MAP_SWIZZLE_NONE, CU_TENSOR_MAP_L2_PROMOTION_NONE);
    cuuint64_t dw[2] = {WROW * 8, 512}, sw[1] = {WROW * 16}; cuuint32_t bw[2] = {32, 64};
    make_map(enc, &mWf, pwf, 2, dw, sw, bw, CU_TENSOR_MAP_SWIZZLE_NONE, CU_TENSOR_MAP_L2_PROMOTION_NONE);
  }
  cudaFuncSetAttribute(fused_kernel, cudaFuncAttributeMaxDynamicSharedMemorySize, SMEM_BYTES);
  fused_kernel<<<132, 384, SMEM_BYTES>>>(mXn, mH, mWg, mWu, mWd, mX, mOut, mZ1, mZ2, mWf, (const __nv_bfloat16*)d_in[0],
                                         (const unsigned short*)d_in[1], (const unsigned short*)d_in[2],
                                         (const __nv_bfloat16*)d_in[4], (const __nv_bfloat16*)d_in[5]);
}
```
